```python
import torch

def _softmax(x, axis=-1):
    return torch.softmax(x, dim=axis)

def _gelu(x):
    return torch.nn.functional.gelu(x, approximate='tanh')

def _silu(x):
    return torch.nn.functional.silu(x)

def _sigmoid(x):
    return torch.sigmoid(x)

def _layernorm(x, axis=-1, eps=1e-05):
    m = x.mean(dim=axis, keepdim=True)
    v = x.var(dim=axis, keepdim=True, unbiased=False)
    return (x - m) / torch.sqrt(v + eps)

def _scatter_add(tgt, idx, src, axis=0):
    return tgt.clone().index_add_(axis, idx, src)

def _segment_sum(src, seg, n):
    out = torch.zeros((n,) + src.shape[1:], dtype=src.dtype)
    return out.index_add_(0, seg, src)

def _pad(x, pw):
    flat = tuple((v for pair in reversed(pw) for v in pair))
    return torch.nn.functional.pad(x, flat)
kernel_name = 'interleave_layers__memory_aug_recurrent_mem_tr__sliding_local_dilated__prompt'

def setup_inputs():

    _w = lambda a: (lambda t: t.to(torch.bfloat16) if t.is_floating_point() else t)(torch.as_tensor(a))

    def _A_setup():
        B, S, Dm = (1, 2048, 640)
        H, Dh = (32, 192)
        M, seg = (8, 32)
        seg = min(seg, S)
        S = S // seg * seg
        return {'x': _w((lambda *s: torch.randn(*s, dtype=torch.bfloat16) * 0.05)(B, S, Dm)), 'mem0': _w((lambda *s: torch.randn(*s, dtype=torch.bfloat16) * 0.8)(B, M, Dm)), 'Wq': _w((lambda *s: torch.randn(*s, dtype=torch.bfloat16) * 1.6)(Dm, H, Dh) * Dm ** (-0.5)), 'Wk': _w((lambda *s: torch.randn(*s, dtype=torch.bfloat16) * 1.6)(Dm, H, Dh) * Dm ** (-0.5)), 'Wv': _w((lambda *s: torch.randn(*s, dtype=torch.bfloat16) * 0.8)(Dm, H, Dh) * Dm ** (-0.5)), 'Wo': _w((lambda *s: torch.randn(*s, dtype=torch.bfloat16) * 0.8)(H, Dh, Dm) * (H * Dh) ** (-0.5)), 'seg_len': seg}
    _A_in = _A_setup()

    def _B_setup():
        B, S, D = (1, 2048, 640)
        return {'x': _w((lambda *s: torch.randn(*s, dtype=torch.bfloat16) * 0.05)(B, S, D)), 'wqkv': _w((lambda *s: torch.randn(*s, dtype=torch.bfloat16) * 0.05)(D, 3 * D)), 'wo': _w((lambda *s: torch.randn(*s, dtype=torch.bfloat16) * 0.05)(D, D))}
    _B_in = _B_setup()
    return {'A_x': _A_in['x'], 'A_mem0': _A_in['mem0'], 'A_Wq': _A_in['Wq'], 'A_Wk': _A_in['Wk'], 'A_Wv': _A_in['Wv'], 'A_Wo': _A_in['Wo'], 'A_seg_len': _A_in['seg_len'], 'B_x': _B_in['x'], 'B_wqkv': _B_in['wqkv'], 'B_wo': _B_in['wo']}

def reference(A_x, A_mem0, A_Wq, A_Wk, A_Wv, A_Wo, A_seg_len, B_x, B_wqkv, B_wo):

    def _A_ref(x, mem0, Wq, Wk, Wv, Wo, seg_len):
        B, S, Dm = x.shape
        H, Dh = (Wq.shape[1], Wq.shape[2])
        M = mem0.shape[1]
        scale = Dh ** (-0.5)
        n_seg = S // seg_len
        L = M + seg_len
        idx = torch.arange(L)
        mask = (idx[:, None] < M) | (idx[:, None] >= idx[None, :])
        mem = mem0
        outs = []
        for s in range(n_seg):
            xs = x[:, s * seg_len:(s + 1) * seg_len, :].clone()
            h = torch.concatenate([mem, xs], axis=1)
            q = torch.einsum('btd,dhe->bhte', h, Wq)
            k = torch.einsum('btd,dhe->bhte', h, Wk)
            v = torch.einsum('btd,dhe->bhte', h, Wv)
            scores = torch.einsum('bhqe,bhke->bhqk', q, k) * scale
            scores = torch.where(mask[None, None], scores, -1000000000.0)
            p = _softmax(scores, axis=-1)
            o = torch.einsum('bhqk,bhke->bhqe', p, v)
            o = torch.einsum('bhte,hed->btd', o, Wo)
            mem = o[:, :M, :].clone()
            outs.append(o[:, M:, :])
        return torch.concatenate(outs, axis=1)

    def _B_ref(x, wqkv, wo):
        B, S, D = x.shape
        H = 32
        Dh = D // H
        W, dil = (8, 2)
        qkv = (lambda x, *d: x.permute(*d))((x @ wqkv).reshape(B, S, 3, H, Dh), 2, 0, 3, 1, 4)
        q, k, v = (qkv[0], qkv[1], qkv[2])
        scale = Dh ** (-0.5)
        pos = torch.arange(S)
        off = torch.arange(W) * dil
        idx = pos[:, None] - off[None, :]
        mask = idx >= 0
        idx_c = torch.where(mask, idx, 0).reshape(-1)
        kg = k[:, :, idx_c, :].reshape(B, H, S, W, Dh)
        vg = v[:, :, idx_c, :].reshape(B, H, S, W, Dh)
        logits = torch.einsum('bhsd,bhswd->bhsw', q, kg) * scale
        logits = torch.where(mask[None, None, :, :], logits, -1000000000.0)
        attn = _softmax(logits, axis=-1)
        o = torch.einsum('bhsw,bhswd->bhsd', attn, vg)
        return (lambda x, *d: x.permute(*d))(o, 0, 2, 1, 3).reshape(B, S, D) @ wo
    x = A_x
    x = x + _A_ref(_layernorm(x, axis=-1), A_mem0, A_Wq, A_Wk, A_Wv, A_Wo, A_seg_len)
    x = x + _B_ref(_layernorm(x, axis=-1), B_wqkv, B_wo)
    x = x + _A_ref(_layernorm(x, axis=-1), A_mem0, A_Wq, A_Wk, A_Wv, A_Wo, A_seg_len)
    x = x + _B_ref(_layernorm(x, axis=-1), B_wqkv, B_wo)
    return x
```

```cpp
#include <cuda_runtime.h>
#include <cuda_bf16.h>
#include <cuda.h>
#include <stdint.h>

typedef __nv_bfloat16 bf16;

constexpr int SEQ = 2048, DM = 640, NH = 32, DH = 192, NSEG = 64;
#define LAG 14
constexpr int NS = NSEG + LAG;
constexpr uint32_t SENT = 0xFFFFFFFFu;
constexpr int SPIN_BUDGET = 1 << 23;

constexpr int MAIL_UNIT = 65536, NUNIT = 88;
__device__ __align__(1024) uint8_t g_xn[2][32 * 10 * 8192];
__device__ __align__(1024) uint8_t g_xnb[2][32 * 10 * 8192];
__device__ __align__(1024) uint8_t g_ob[2][32 * 10 * 8192];
__device__ __align__(1024) uint8_t g_o[2][32 * 96 * 8192];
__device__ __align__(8192) uint8_t g_mbuf[3][40960];
__device__ __align__(8192) uint8_t g_mail[NUNIT + 1][MAIL_UNIT];
__device__ uint32_t g_sel[NUNIT];
__device__ __align__(1024) uint8_t g_rot[96][32768];
__device__ __align__(1024) float g_acc[2][16][5][16384];
__device__ __align__(1024) float2 g_stats[16][128][16];
__device__ __align__(128) bf16 g_x1[SEQ * DM];
__device__ __align__(128) bf16 g_x2[SEQ * DM];
__device__ __align__(128) bf16 g_x3[SEQ * DM];
enum { CN_O = 0, CN_P = 1, CN_L = 2, CN_A = 3, CN_X = 4, CN_Z = 5 };
__device__ __align__(128) uint32_t g_cnt[6][2][16][32];
__device__ int g_err;
#define DUR(i)
#define TS(jj, i)
#define PTS(i)
#define TSB(jj, i)
#define TSV(jj, i, v)
#define TS_FLUSH(jj)
#define WTS(l, b, k)
#define WW -1

__device__ __forceinline__ uint32_t smem_u32(const void* p) { return (uint32_t)__cvta_generic_to_shared(p); }
__device__ __forceinline__ uint32_t clk32() { unsigned long long t; asm volatile("mov.u64 %0, %%clock64;" : "=l"(t)::"memory"); return (uint32_t)t; }
__device__ __forceinline__ uint32_t mapa(uint32_t a, uint32_t r) { uint32_t o; asm("mapa.shared::cluster.u32 %0,%1,%2;" : "=r"(o) : "r"(a), "r"(r)); return o; }
__device__ __forceinline__ void mbar_init(uint32_t bar, uint32_t cnt) { asm volatile("mbarrier.init.shared::cta.b64 [%0],%1;" ::"r"(bar), "r"(cnt) : "memory"); }
__device__ __forceinline__ void mbar_expect_tx(uint32_t bar, uint32_t bytes) { asm volatile("mbarrier.arrive.expect_tx.shared::cta.b64 _,[%0],%1;" ::"r"(bar), "r"(bytes) : "memory"); }
__device__ __forceinline__ void mbar_arrive(uint32_t bar) { asm volatile("mbarrier.arrive.shared::cta.b64 _,[%0];" ::"r"(bar) : "memory"); }
__device__ __forceinline__ void mbar_arrive_cluster(uint32_t bar) { asm volatile("mbarrier.arrive.shared::cluster.b64 _,[%0];" ::"r"(bar) : "memory"); }
__device__ __forceinline__ bool mbar_try(uint32_t bar, uint32_t ph) {
  uint32_t ok;
  asm volatile("{.reg .pred p; mbarrier.try_wait.parity.shared::cta.b64 p,[%1],%2; selp.u32 %0,1,0,p;}" : "=r"(ok) : "r"(bar), "r"(ph) : "memory");
  return ok;
}
__device__ __forceinline__ bool mbar_test(uint32_t bar, uint32_t ph) {
  uint32_t ok;
  asm volatile("{.reg .pred p; mbarrier.test_wait.parity.shared::cta.b64 p,[%1],%2; selp.u32 %0,1,0,p;}" : "=r"(ok) : "r"(bar), "r"(ph) : "memory");
  return ok;
}
__device__ __forceinline__ void mbar_wait(uint32_t bar, uint32_t ph, int& left) {
  asm volatile("{\n.reg .pred p;\nW: mbarrier.try_wait.parity.shared::cta.b64 p,[%1],%2;\nadd.s32 %0,%0,-1;\nsetp.gt.and.s32 p,%0,0,!p;\n@p bra.uni W;\n}"
               : "+r"(left) : "r"(bar), "r"(ph) : "memory");
}
__device__ __forceinline__ bool elect() {
  uint32_t p;
  asm volatile("{.reg .pred p; elect.sync _|p,0xffffffff; selp.u32 %0,1,0,p;}" : "=r"(p));
  return p;
}
__device__ __forceinline__ int fresh(int x) { asm volatile("" : "+r"(x)); return x; }
__device__ __forceinline__ void bar_sync(int id, int n) { asm volatile("bar.sync %0,%1;" ::"r"(id), "r"(n) : "memory"); }
__device__ __forceinline__ void bar_arrive(int id, int n) { asm volatile("bar.arrive %0,%1;" ::"r"(id), "r"(n) : "memory"); }
__device__ __forceinline__ bool bar_red_or(int id, int n, bool v) {
  uint32_t r;
  asm volatile("{\n .reg .pred p, q;\n setp.ne.u32 q, %3, 0;\n barrier.cta.red.or.pred p, %1, %2, q;\n selp.u32 %0, 1, 0, p;\n}" : "=r"(r) : "r"(id), "r"(n), "r"((uint32_t)v) : "memory");
  return r != 0;
}
__device__ __forceinline__ void cluster_sync() {
  asm volatile("barrier.cluster.arrive.release.aligned;" ::: "memory");
  asm volatile("barrier.cluster.wait.acquire.aligned;" ::: "memory");
}
__device__ __forceinline__ void fence_async() { asm volatile("fence.proxy.async.shared::cta;" ::: "memory"); }
__device__ __forceinline__ void bulk_g2s(uint32_t dst, const void* src, uint32_t bytes, uint32_t bar) {
  asm volatile("cp.async.bulk.shared::cluster.global.mbarrier::complete_tx::bytes [%0],[%1],%2,[%3];" ::"r"(dst), "l"(src), "r"(bytes), "r"(bar) : "memory");
}
__device__ __forceinline__ void bulk_g2s_mc(uint32_t dst, const void* src, uint32_t bytes, uint32_t bar) {
  asm volatile("cp.async.bulk.shared::cluster.global.mbarrier::complete_tx::bytes.multicast::cluster [%0],[%1],%2,[%3],%4;"
               ::"r"(dst), "l"(src), "r"(bytes), "r"(bar), "h"((uint16_t)7) : "memory");
}
__device__ __forceinline__ void bulk_s2g(void* dst, uint32_t src, uint32_t bytes) {
  asm volatile("cp.async.bulk.global.shared::cta.bulk_group [%0],[%1],%2;" ::"l"(dst), "r"(src), "r"(bytes) : "memory");
}
__device__ __forceinline__ void bulk_s2c(uint32_t dst, uint32_t src, uint32_t bytes, uint32_t bar) {
  asm volatile("cp.async.bulk.shared::cluster.shared::cta.mbarrier::complete_tx::bytes [%0],[%1],%2,[%3];" ::"r"(dst), "r"(src), "r"(bytes), "r"(bar) : "memory");
}
__device__ __forceinline__ void bulk_commit() { asm volatile("cp.async.bulk.commit_group;" ::: "memory"); }
__device__ __forceinline__ void bulk_wait_read() { asm volatile("cp.async.bulk.wait_group.read 0;" ::: "memory"); }
__device__ __forceinline__ void bulk_wait() { asm volatile("cp.async.bulk.wait_group 0;" ::: "memory"); }
__device__ __forceinline__ void tma2d(uint32_t dst, const CUtensorMap* tm, int c0, int c1, uint32_t bar) {
  asm volatile("cp.async.bulk.tensor.2d.shared::cluster.global.mbarrier::complete_tx::bytes [%0],[%1,{%3,%4}],[%2];"
               ::"r"(dst), "l"(tm), "r"(bar), "r"(c0), "r"(c1) : "memory");
}
__device__ __forceinline__ void tma3d_mc(uint32_t dst, const CUtensorMap* tm, int c0, int c1, int c2, uint32_t bar) {
  asm volatile("cp.async.bulk.tensor.3d.shared::cluster.global.mbarrier::complete_tx::bytes.multicast::cluster [%0],[%1,{%3,%4,%5}],[%2],%6;"
               ::"r"(dst), "l"(tm), "r"(bar), "r"(c0), "r"(c1), "r"(c2), "h"((uint16_t)7) : "memory");
}
__device__ __forceinline__ uint32_t pack_bf16(float lo, float hi) {
  uint32_t r; asm("cvt.rn.bf16x2.f32 %0,%1,%2;" : "=r"(r) : "f"(hi), "f"(lo)); return r;
}
__device__ __forceinline__ uint32_t pack_h2(float lo, float hi) {
  uint32_t r; asm("cvt.rn.satfinite.f16x2.f32 %0,%1,%2;" : "=r"(r) : "f"(hi), "f"(lo)); return r;
}
__device__ __forceinline__ float2 unpack_h2(uint32_t x) {
  float2 r; asm("{.reg .b16 l,h; mov.b32 {l,h},%2; cvt.f32.f16 %0,l; cvt.f32.f16 %1,h;}" : "=f"(r.x), "=f"(r.y) : "r"(x)); return r;
}
__device__ __forceinline__ uint32_t add_h2(uint32_t a, uint32_t b) { uint32_t r; asm("add.rn.f16x2 %0,%1,%2;" : "=r"(r) : "r"(a), "r"(b)); return r; }
__device__ __forceinline__ uint32_t max_h2(uint32_t a, uint32_t b) { uint32_t r; asm("max.f16x2 %0,%1,%2;" : "=r"(r) : "r"(a), "r"(b)); return r; }
__device__ __forceinline__ float bf_lo(uint32_t x) { return __uint_as_float(x << 16); }
__device__ __forceinline__ float bf_hi(uint32_t x) { return __uint_as_float(x & 0xFFFF0000u); }
__device__ __forceinline__ float ex2(float x) { float y; asm("ex2.approx.ftz.f32 %0,%1;" : "=f"(y) : "f"(x)); return y; }
__device__ __forceinline__ void ldsm4t(uint32_t (&r)[4], uint32_t a) {
  asm volatile("ldmatrix.sync.aligned.m8n8.x4.trans.shared.b16 {%0,%1,%2,%3},[%4];" : "=r"(r[0]), "=r"(r[1]), "=r"(r[2]), "=r"(r[3]) : "r"(a) : "memory");
}
__device__ __forceinline__ void stsm4(uint32_t a, uint32_t r0, uint32_t r1, uint32_t r2, uint32_t r3) {
  asm volatile("stmatrix.sync.aligned.m8n8.x4.shared.b16 [%0],{%1,%2,%3,%4};" ::"r"(a), "r"(r0), "r"(r1), "r"(r2), "r"(r3) : "memory");
}
__device__ __forceinline__ void stsm4t(uint32_t a, uint32_t r0, uint32_t r1, uint32_t r2, uint32_t r3) {
  asm volatile("stmatrix.sync.aligned.m8n8.x4.trans.shared.b16 [%0],{%1,%2,%3,%4};" ::"r"(a), "r"(r0), "r"(r1), "r"(r2), "r"(r3) : "memory");
}
__device__ __forceinline__ void stsm2(uint32_t a, uint32_t r0, uint32_t r1) {
  asm volatile("stmatrix.sync.aligned.m8n8.x2.shared.b16 [%0],{%1,%2};" ::"r"(a), "r"(r0), "r"(r1) : "memory");
}
__device__ __forceinline__ void sts32(uint32_t a, uint32_t v) { asm volatile("st.shared.b32 [%0],%1;" ::"r"(a), "r"(v) : "memory"); }
__device__ __forceinline__ void sts128(uint32_t a, uint4 v) { asm volatile("st.shared.v4.b32 [%0],{%1,%2,%3,%4};" ::"r"(a), "r"(v.x), "r"(v.y), "r"(v.z), "r"(v.w) : "memory"); }
__device__ __forceinline__ uint32_t lds32(uint32_t a) { uint32_t v; asm volatile("ld.shared.b32 %0,[%1];" : "=r"(v) : "r"(a) : "memory"); return v; }
__device__ __forceinline__ uint2 lds64(uint32_t a) { uint2 v; asm volatile("ld.shared.v2.b32 {%0,%1},[%2];" : "=r"(v.x), "=r"(v.y) : "r"(a) : "memory"); return v; }
__device__ __forceinline__ uint4 lds128(uint32_t a) { uint4 v; asm volatile("ld.shared.v4.b32 {%0,%1,%2,%3},[%4];" : "=r"(v.x), "=r"(v.y), "=r"(v.z), "=r"(v.w) : "r"(a) : "memory"); return v; }
__device__ __forceinline__ void st_async1(uint32_t a, uint32_t x, uint32_t bar) {
  asm volatile("st.async.weak.shared::cluster.mbarrier::complete_tx::bytes.b32 [%0],%1,[%2];" ::"r"(a), "r"(x), "r"(bar) : "memory");
}
__device__ __forceinline__ void st_async2(uint32_t a, uint32_t x, uint32_t y, uint32_t bar) {
  asm volatile("st.async.weak.shared::cluster.mbarrier::complete_tx::bytes.v2.b32 [%0],{%1,%2},[%3];" ::"r"(a), "r"(x), "r"(y), "r"(bar) : "memory");
}
__device__ __forceinline__ void st_async4(uint32_t a, uint32_t x, uint32_t y, uint32_t z, uint32_t w, uint32_t bar) {
  asm volatile("st.async.weak.shared::cluster.mbarrier::complete_tx::bytes.v4.b32 [%0],{%1,%2,%3,%4},[%5];" ::"r"(a), "r"(x), "r"(y), "r"(z), "r"(w), "r"(bar) : "memory");
}
__device__ __forceinline__ uint32_t ld_relaxed(const void* p) {
  uint32_t v; asm volatile("ld.relaxed.gpu.global.u32 %0,[%1];" : "=r"(v) : "l"(p) : "memory"); return v;
}
__device__ __forceinline__ void st_relaxed(void* p, uint32_t v) { asm volatile("st.relaxed.gpu.global.b32 [%0],%1;" ::"l"(p), "r"(v) : "memory"); }
__device__ __forceinline__ void ld_msg16x4(uint4* x, const void* p) {
  asm volatile("{.reg .b128 a,b,c,d;\n ld.relaxed.gpu.global.b128 a,[%16]; ld.relaxed.gpu.global.b128 b,[%16+512];\n"
               "ld.relaxed.gpu.global.b128 c,[%16+1024]; ld.relaxed.gpu.global.b128 d,[%16+1536];\n"
               "mov.b128 {%0,%1,%2,%3},a; mov.b128 {%4,%5,%6,%7},b; mov.b128 {%8,%9,%10,%11},c; mov.b128 {%12,%13,%14,%15},d;}"
               : "=r"(x[0].x), "=r"(x[0].y), "=r"(x[0].z), "=r"(x[0].w), "=r"(x[1].x), "=r"(x[1].y), "=r"(x[1].z), "=r"(x[1].w),
                 "=r"(x[2].x), "=r"(x[2].y), "=r"(x[2].z), "=r"(x[2].w), "=r"(x[3].x), "=r"(x[3].y), "=r"(x[3].z), "=r"(x[3].w)
               : "l"(p) : "memory");
}
__device__ __forceinline__ uint32_t differ4(uint32_t a, uint32_t b, uint32_t c, uint32_t d, uint32_t t) {
  uint32_t r;
  asm volatile("{.reg .b32 u,v; lop3.b32 u,%1,%2,%5,0x7e; lop3.b32 v,%3,%4,%5,0x7e; or.b32 %0,u,v;}" : "=r"(r) : "r"(a), "r"(b), "r"(c), "r"(d), "r"(t));
  return r;
}
__device__ __forceinline__ void st_msg16(void* p, uint32_t x, uint32_t y, uint32_t z, uint32_t w) {
  asm volatile("{.reg .b128 r; mov.b128 r,{%1,%2,%3,%4}; st.relaxed.gpu.global.b128 [%0],r;}" ::"l"(p), "r"(x), "r"(y), "r"(z), "r"(w) : "memory");
}
__device__ __forceinline__ void ld_msg16x2(uint4* x, const void* p) {
  asm volatile("{.reg .b128 a,b;\n ld.relaxed.gpu.global.b128 a,[%8]; ld.relaxed.gpu.global.b128 b,[%8+512];\n"
               "mov.b128 {%0,%1,%2,%3},a; mov.b128 {%4,%5,%6,%7},b;}"
               : "=r"(x[0].x), "=r"(x[0].y), "=r"(x[0].z), "=r"(x[0].w), "=r"(x[1].x), "=r"(x[1].y), "=r"(x[1].z), "=r"(x[1].w)
               : "l"(p) : "memory");
}
__device__ __forceinline__ void ld_msg16x6(uint4* x, const void* p, const void* q) {
  asm volatile("{.reg .b128 a,b,c,d,e,f;\n ld.relaxed.gpu.global.b128 a,[%24]; ld.relaxed.gpu.global.b128 b,[%24+512];\n"
               "ld.relaxed.gpu.global.b128 c,[%24+1024]; ld.relaxed.gpu.global.b128 d,[%24+1536];\n"
               "ld.relaxed.gpu.global.b128 e,[%25]; ld.relaxed.gpu.global.b128 f,[%25+512];\n"
               "mov.b128 {%0,%1,%2,%3},a; mov.b128 {%4,%5,%6,%7},b; mov.b128 {%8,%9,%10,%11},c; mov.b128 {%12,%13,%14,%15},d;\n"
               "mov.b128 {%16,%17,%18,%19},e; mov.b128 {%20,%21,%22,%23},f;}"
               : "=r"(x[0].x), "=r"(x[0].y), "=r"(x[0].z), "=r"(x[0].w), "=r"(x[1].x), "=r"(x[1].y), "=r"(x[1].z), "=r"(x[1].w),
                 "=r"(x[2].x), "=r"(x[2].y), "=r"(x[2].z), "=r"(x[2].w), "=r"(x[3].x), "=r"(x[3].y), "=r"(x[3].z), "=r"(x[3].w),
                 "=r"(x[4].x), "=r"(x[4].y), "=r"(x[4].z), "=r"(x[4].w), "=r"(x[5].x), "=r"(x[5].y), "=r"(x[5].z), "=r"(x[5].w)
               : "l"(p), "l"(q) : "memory");
}
__device__ __forceinline__ uint32_t ld_acquire(const void* p) {
  uint32_t v; asm volatile("ld.acquire.gpu.global.u32 %0,[%1];" : "=r"(v) : "l"(p) : "memory"); return v;
}
__device__ __forceinline__ float4 ld_relaxed4f(const void* p) {
  float4 v; asm volatile("ld.relaxed.gpu.global.v4.f32 {%0,%1,%2,%3},[%4];" : "=f"(v.x), "=f"(v.y), "=f"(v.z), "=f"(v.w) : "l"(p) : "memory"); return v;
}
__device__ __forceinline__ float2 ld_relaxed2f(const void* p) {
  float2 v; asm volatile("ld.relaxed.gpu.global.v2.f32 {%0,%1},[%2];" : "=f"(v.x), "=f"(v.y) : "l"(p) : "memory"); return v;
}
__device__ __forceinline__ void prefetch_l2(const void* p) { asm volatile("prefetch.global.L2 [%0];" ::"l"(p)); }
__device__ __forceinline__ void fence_async_all() { asm volatile("fence.proxy.async.global;" ::: "memory"); }
__device__ __forceinline__ uint32_t* cnt_ptr(int kind, int layer, int b) { return &g_cnt[kind][layer][b][0]; }
__device__ __forceinline__ void cnt_signal(int kind, int layer, int b) {
  asm volatile("red.release.gpu.global.add.u32 [%0],1;" ::"l"(cnt_ptr(kind, layer, b)) : "memory");
}
__device__ __forceinline__ void cnt_wait(int kind, int layer, int b, uint32_t target, int& left) {
  while (ld_acquire(cnt_ptr(kind, layer, b)) < target && (left -= 16) > 0) {}
}

__host__ __device__ __forceinline__ constexpr uint64_t mkdesc(uint32_t addr, uint32_t lbo, uint32_t sbo) {
  return (uint64_t)((addr & 0x3FFFF) >> 4) | ((uint64_t)(lbo >> 4) << 16) | ((uint64_t)(sbo >> 4) << 32) | ((uint64_t)1 << 62);
}
__host__ __device__ __forceinline__ constexpr uint64_t mkdesc64(uint32_t addr, uint32_t lbo, uint32_t sbo) {
  return (uint64_t)((addr & 0x3FFFF) >> 4) | ((uint64_t)(lbo >> 4) << 16) | ((uint64_t)(sbo >> 4) << 32) | ((uint64_t)2 << 62);
}
__host__ __device__ __forceinline__ constexpr uint64_t mkdesc_ns(uint32_t addr, uint32_t lbo, uint32_t sbo) {
  return (uint64_t)((addr & 0x3FFFF) >> 4) | ((uint64_t)(lbo >> 4) << 16) | ((uint64_t)(sbo >> 4) << 32);
}
__device__ __forceinline__ void wg_fence() { asm volatile("wgmma.fence.sync.aligned;" ::: "memory"); }
__device__ __forceinline__ void wg_commit() { asm volatile("wgmma.commit_group.sync.aligned;" ::: "memory"); }
template <int N> __device__ __forceinline__ void wg_wait() { asm volatile("wgmma.wait_group.sync.aligned %0;" ::"n"(N) : "memory"); }

__device__ __forceinline__ void wgmma_rs32(float (&d)[16], const uint32_t (&a)[4], uint64_t db, int sc) {
  asm volatile("{.reg .pred p; setp.ne.b32 p,%21,0; wgmma.mma_async.sync.aligned.m64n32k16.f32.bf16.bf16 "
               "{%0,%1,%2,%3,%4,%5,%6,%7,%8,%9,%10,%11,%12,%13,%14,%15},{%16,%17,%18,%19},%20,p,1,1,0;}"
               : "+f"(d[0]), "+f"(d[1]), "+f"(d[2]), "+f"(d[3]), "+f"(d[4]), "+f"(d[5]), "+f"(d[6]), "+f"(d[7]),
                 "+f"(d[8]), "+f"(d[9]), "+f"(d[10]), "+f"(d[11]), "+f"(d[12]), "+f"(d[13]), "+f"(d[14]), "+f"(d[15])
               : "r"(a[0]), "r"(a[1]), "r"(a[2]), "r"(a[3]), "l"(db), "r"(sc));
}
__device__ __forceinline__ void wgmma_rs48(float (&d)[24], const uint32_t (&a)[4], uint64_t db, int sc) {
  asm volatile("{.reg .pred p; setp.ne.b32 p,%29,0; wgmma.mma_async.sync.aligned.m64n48k16.f32.bf16.bf16 "
               "{%0,%1,%2,%3,%4,%5,%6,%7,%8,%9,%10,%11,%12,%13,%14,%15,%16,%17,%18,%19,%20,%21,%22,%23},{%24,%25,%26,%27},%28,p,1,1,0;}"
               : "+f"(d[0]), "+f"(d[1]), "+f"(d[2]), "+f"(d[3]), "+f"(d[4]), "+f"(d[5]), "+f"(d[6]), "+f"(d[7]),
                 "+f"(d[8]), "+f"(d[9]), "+f"(d[10]), "+f"(d[11]), "+f"(d[12]), "+f"(d[13]), "+f"(d[14]), "+f"(d[15]),
                 "+f"(d[16]), "+f"(d[17]), "+f"(d[18]), "+f"(d[19]), "+f"(d[20]), "+f"(d[21]), "+f"(d[22]), "+f"(d[23])
               : "r"(a[0]), "r"(a[1]), "r"(a[2]), "r"(a[3]), "l"(db), "r"(sc));
}
__device__ __forceinline__ void wgmma_ts32(float (&d)[16], uint64_t da, uint64_t db, int sc) {
  asm volatile("{.reg .pred p; setp.ne.b32 p,%18,0; wgmma.mma_async.sync.aligned.m64n32k16.f32.bf16.bf16 "
               "{%0,%1,%2,%3,%4,%5,%6,%7,%8,%9,%10,%11,%12,%13,%14,%15},%16,%17,p,1,1,1,0;}"
               : "+f"(d[0]), "+f"(d[1]), "+f"(d[2]), "+f"(d[3]), "+f"(d[4]), "+f"(d[5]), "+f"(d[6]), "+f"(d[7]),
                 "+f"(d[8]), "+f"(d[9]), "+f"(d[10]), "+f"(d[11]), "+f"(d[12]), "+f"(d[13]), "+f"(d[14]), "+f"(d[15])
               : "l"(da), "l"(db), "r"(sc));
}
__device__ __forceinline__ void wgmma_ts48(float (&d)[24], uint64_t da, uint64_t db, int sc) {
  asm volatile("{.reg .pred p; setp.ne.b32 p,%26,0; wgmma.mma_async.sync.aligned.m64n48k16.f32.bf16.bf16 "
               "{%0,%1,%2,%3,%4,%5,%6,%7,%8,%9,%10,%11,%12,%13,%14,%15,%16,%17,%18,%19,%20,%21,%22,%23},%24,%25,p,1,1,1,0;}"
               : "+f"(d[0]), "+f"(d[1]), "+f"(d[2]), "+f"(d[3]), "+f"(d[4]), "+f"(d[5]), "+f"(d[6]), "+f"(d[7]),
                 "+f"(d[8]), "+f"(d[9]), "+f"(d[10]), "+f"(d[11]), "+f"(d[12]), "+f"(d[13]), "+f"(d[14]), "+f"(d[15]),
                 "+f"(d[16]), "+f"(d[17]), "+f"(d[18]), "+f"(d[19]), "+f"(d[20]), "+f"(d[21]), "+f"(d[22]), "+f"(d[23])
               : "l"(da), "l"(db), "r"(sc));
}
__device__ __forceinline__ void wgmma_tt40(float (&d)[20], uint64_t da, uint64_t db, int sc) {
  asm volatile("{.reg .pred p; setp.ne.b32 p,%22,0; wgmma.mma_async.sync.aligned.m64n40k16.f32.bf16.bf16 "
               "{%0,%1,%2,%3,%4,%5,%6,%7,%8,%9,%10,%11,%12,%13,%14,%15,%16,%17,%18,%19},%20,%21,p,1,1,1,1;}"
               : "+f"(d[0]), "+f"(d[1]), "+f"(d[2]), "+f"(d[3]), "+f"(d[4]), "+f"(d[5]), "+f"(d[6]), "+f"(d[7]),
                 "+f"(d[8]), "+f"(d[9]), "+f"(d[10]), "+f"(d[11]), "+f"(d[12]), "+f"(d[13]), "+f"(d[14]), "+f"(d[15]),
                 "+f"(d[16]), "+f"(d[17]), "+f"(d[18]), "+f"(d[19])
               : "l"(da), "l"(db), "r"(sc));
}
__device__ __forceinline__ void wgmma_ss8(float (&d)[4], uint64_t da, uint64_t db, int sc) {
  asm volatile("{.reg .pred p; setp.ne.b32 p,%6,0; wgmma.mma_async.sync.aligned.m64n8k16.f32.bf16.bf16 "
               "{%0,%1,%2,%3},%4,%5,p,1,1,0,0;}"
               : "+f"(d[0]), "+f"(d[1]), "+f"(d[2]), "+f"(d[3])
               : "l"(da), "l"(db), "r"(sc));
}
__device__ __forceinline__ void wgmma_ss32(float (&d)[16], uint64_t da, uint64_t db, int sc) {
  asm volatile("{.reg .pred p; setp.ne.b32 p,%18,0; wgmma.mma_async.sync.aligned.m64n32k16.f32.bf16.bf16 "
               "{%0,%1,%2,%3,%4,%5,%6,%7,%8,%9,%10,%11,%12,%13,%14,%15},%16,%17,p,1,1,0,0;}"
               : "+f"(d[0]), "+f"(d[1]), "+f"(d[2]), "+f"(d[3]), "+f"(d[4]), "+f"(d[5]), "+f"(d[6]), "+f"(d[7]),
                 "+f"(d[8]), "+f"(d[9]), "+f"(d[10]), "+f"(d[11]), "+f"(d[12]), "+f"(d[13]), "+f"(d[14]), "+f"(d[15])
               : "l"(da), "l"(db), "r"(sc));
}
__device__ __forceinline__ void wgmma_tt16(float (&d)[8], uint64_t da, uint64_t db, int sc) {
  asm volatile("{.reg .pred p; setp.ne.b32 p,%10,0; wgmma.mma_async.sync.aligned.m64n16k16.f32.bf16.bf16 "
               "{%0,%1,%2,%3,%4,%5,%6,%7},%8,%9,p,1,1,1,1;}"
               : "+f"(d[0]), "+f"(d[1]), "+f"(d[2]), "+f"(d[3]), "+f"(d[4]), "+f"(d[5]), "+f"(d[6]), "+f"(d[7])
               : "l"(da), "l"(db), "r"(sc));
}
__device__ __forceinline__ void wgmma_st64(float (&d)[32], uint64_t da, uint64_t db, int sc) {
  asm volatile("{.reg .pred p; setp.ne.b32 p,%34,0; wgmma.mma_async.sync.aligned.m64n64k16.f32.bf16.bf16 "
               "{%0,%1,%2,%3,%4,%5,%6,%7,%8,%9,%10,%11,%12,%13,%14,%15,%16,%17,%18,%19,%20,%21,%22,%23,%24,%25,%26,%27,%28,%29,%30,%31},%32,%33,p,1,1,0,1;}"
               : "+f"(d[0]), "+f"(d[1]), "+f"(d[2]), "+f"(d[3]), "+f"(d[4]), "+f"(d[5]), "+f"(d[6]), "+f"(d[7]),
                 "+f"(d[8]), "+f"(d[9]), "+f"(d[10]), "+f"(d[11]), "+f"(d[12]), "+f"(d[13]), "+f"(d[14]), "+f"(d[15]),
                 "+f"(d[16]), "+f"(d[17]), "+f"(d[18]), "+f"(d[19]), "+f"(d[20]), "+f"(d[21]), "+f"(d[22]), "+f"(d[23]),
                 "+f"(d[24]), "+f"(d[25]), "+f"(d[26]), "+f"(d[27]), "+f"(d[28]), "+f"(d[29]), "+f"(d[30]), "+f"(d[31])
               : "l"(da), "l"(db), "r"(sc));
}
__device__ __forceinline__ void wgmma_st128(float (&d)[64], uint64_t da, uint64_t db, int sc) {
  asm volatile("{.reg .pred p; setp.ne.b32 p,%66,0; wgmma.mma_async.sync.aligned.m64n128k16.f32.bf16.bf16 "
               "{%0,%1,%2,%3,%4,%5,%6,%7,%8,%9,%10,%11,%12,%13,%14,%15,%16,%17,%18,%19,%20,%21,%22,%23,%24,%25,%26,%27,%28,%29,%30,%31,%32,%33,%34,%35,%36,%37,%38,%39,%40,%41,%42,%43,%44,%45,%46,%47,%48,%49,%50,%51,%52,%53,%54,%55,%56,%57,%58,%59,%60,%61,%62,%63},%64,%65,p,1,1,0,1;}"
               : "+f"(d[0]), "+f"(d[1]), "+f"(d[2]), "+f"(d[3]), "+f"(d[4]), "+f"(d[5]), "+f"(d[6]), "+f"(d[7]),
                 "+f"(d[8]), "+f"(d[9]), "+f"(d[10]), "+f"(d[11]), "+f"(d[12]), "+f"(d[13]), "+f"(d[14]), "+f"(d[15]),
                 "+f"(d[16]), "+f"(d[17]), "+f"(d[18]), "+f"(d[19]), "+f"(d[20]), "+f"(d[21]), "+f"(d[22]), "+f"(d[23]),
                 "+f"(d[24]), "+f"(d[25]), "+f"(d[26]), "+f"(d[27]), "+f"(d[28]), "+f"(d[29]), "+f"(d[30]), "+f"(d[31]),
                 "+f"(d[32]), "+f"(d[33]), "+f"(d[34]), "+f"(d[35]), "+f"(d[36]), "+f"(d[37]), "+f"(d[38]), "+f"(d[39]),
                 "+f"(d[40]), "+f"(d[41]), "+f"(d[42]), "+f"(d[43]), "+f"(d[44]), "+f"(d[45]), "+f"(d[46]), "+f"(d[47]),
                 "+f"(d[48]), "+f"(d[49]), "+f"(d[50]), "+f"(d[51]), "+f"(d[52]), "+f"(d[53]), "+f"(d[54]), "+f"(d[55]),
                 "+f"(d[56]), "+f"(d[57]), "+f"(d[58]), "+f"(d[59]), "+f"(d[60]), "+f"(d[61]), "+f"(d[62]), "+f"(d[63])
               : "l"(da), "l"(db), "r"(sc));
}
__device__ __forceinline__ void wgmma_tt128(float (&d)[64], uint64_t da, uint64_t db, int sc) {
  asm volatile("{.reg .pred p; setp.ne.b32 p,%66,0; wgmma.mma_async.sync.aligned.m64n128k16.f32.bf16.bf16 "
               "{%0,%1,%2,%3,%4,%5,%6,%7,%8,%9,%10,%11,%12,%13,%14,%15,%16,%17,%18,%19,%20,%21,%22,%23,%24,%25,%26,%27,%28,%29,%30,%31,%32,%33,%34,%35,%36,%37,%38,%39,%40,%41,%42,%43,%44,%45,%46,%47,%48,%49,%50,%51,%52,%53,%54,%55,%56,%57,%58,%59,%60,%61,%62,%63},%64,%65,p,1,1,1,1;}"
               : "+f"(d[0]), "+f"(d[1]), "+f"(d[2]), "+f"(d[3]), "+f"(d[4]), "+f"(d[5]), "+f"(d[6]), "+f"(d[7]),
                 "+f"(d[8]), "+f"(d[9]), "+f"(d[10]), "+f"(d[11]), "+f"(d[12]), "+f"(d[13]), "+f"(d[14]), "+f"(d[15]),
                 "+f"(d[16]), "+f"(d[17]), "+f"(d[18]), "+f"(d[19]), "+f"(d[20]), "+f"(d[21]), "+f"(d[22]), "+f"(d[23]),
                 "+f"(d[24]), "+f"(d[25]), "+f"(d[26]), "+f"(d[27]), "+f"(d[28]), "+f"(d[29]), "+f"(d[30]), "+f"(d[31]),
                 "+f"(d[32]), "+f"(d[33]), "+f"(d[34]), "+f"(d[35]), "+f"(d[36]), "+f"(d[37]), "+f"(d[38]), "+f"(d[39]),
                 "+f"(d[40]), "+f"(d[41]), "+f"(d[42]), "+f"(d[43]), "+f"(d[44]), "+f"(d[45]), "+f"(d[46]), "+f"(d[47]),
                 "+f"(d[48]), "+f"(d[49]), "+f"(d[50]), "+f"(d[51]), "+f"(d[52]), "+f"(d[53]), "+f"(d[54]), "+f"(d[55]),
                 "+f"(d[56]), "+f"(d[57]), "+f"(d[58]), "+f"(d[59]), "+f"(d[60]), "+f"(d[61]), "+f"(d[62]), "+f"(d[63])
               : "l"(da), "l"(db), "r"(sc));
}

__device__ __forceinline__ void ln_row_to_image(const bf16* __restrict__ x, uint4* st, int row, int lane) {
  const uint4* src = reinterpret_cast<const uint4*>(x + (size_t)row * DM);
  uint4 v[3];
  v[0] = src[lane]; v[1] = src[lane + 32];
  v[2] = lane < 16 ? src[lane + 64] : make_uint4(0, 0, 0, 0);
  float s = 0.f;
#pragma unroll
  for (int i = 0; i < 3; i++) {
    s += bf_lo(v[i].x) + bf_hi(v[i].x) + bf_lo(v[i].y) + bf_hi(v[i].y) + bf_lo(v[i].z) + bf_hi(v[i].z) + bf_lo(v[i].w) + bf_hi(v[i].w);
  }
#pragma unroll
  for (int o = 16; o > 0; o >>= 1) s += __shfl_xor_sync(0xffffffffu, s, o);
  const float mean = s * (1.f / DM);
  float q = 0.f;
#pragma unroll
  for (int i = 0; i < 3; i++) {
    if (i < 2 || lane < 16) {
      const uint32_t w[4] = {v[i].x, v[i].y, v[i].z, v[i].w};
#pragma unroll
      for (int j = 0; j < 4; j++) { float a = bf_lo(w[j]) - mean, b = bf_hi(w[j]) - mean; q += a * a + b * b; }
    }
  }
#pragma unroll
  for (int o = 16; o > 0; o >>= 1) q += __shfl_xor_sync(0xffffffffu, q, o);
  const float rstd = rsqrtf(q * (1.f / DM) + 1e-5f);
#pragma unroll
  for (int i = 0; i < 3; i++) {
    if (i < 2 || lane < 16) {
      const int c = lane + 32 * i;
      uint4 o;
      o.x = pack_bf16((bf_lo(v[i].x) - mean) * rstd, (bf_hi(v[i].x) - mean) * rstd);
      o.y = pack_bf16((bf_lo(v[i].y) - mean) * rstd, (bf_hi(v[i].y) - mean) * rstd);
      o.z = pack_bf16((bf_lo(v[i].z) - mean) * rstd, (bf_hi(v[i].z) - mean) * rstd);
      o.w = pack_bf16((bf_lo(v[i].w) - mean) * rstd, (bf_hi(v[i].w) - mean) * rstd);
      st[c * 8 + ((row ^ c) & 7)] = o;
    }
  }
}

__global__ void __launch_bounds__(256) k_pre(const bf16* __restrict__ x, const bf16* __restrict__ mem0) {
  const int row = blockIdx.x * 8 + (threadIdx.x >> 5);
  __shared__ uint4 st[640];
  ln_row_to_image(x, st, row, threadIdx.x & 31);
  __syncthreads();
  for (int i = threadIdx.x; i < 640; i += 256) reinterpret_cast<uint4*>(g_xn[0])[blockIdx.x * 640 + i] = st[(i & ~7) | ((i ^ (i >> 3)) & 7)];
  const int gt = blockIdx.x * 256 + threadIdx.x;
  const uint4 sent = make_uint4(SENT, SENT, SENT, SENT);
  if (gt < NUNIT) g_sel[gt] = 0;
  if (gt < 3 * 2560) {
    const int i = gt % 2560, p = ((i >> 9) * 256 + (i & 255)) % 640;
    reinterpret_cast<uint4*>(&g_mbuf[0][0])[gt] = gt < 5120 ? sent : *reinterpret_cast<const uint4*>(mem0 + (p & 7) * DM + (p >> 3) * 8);
  }
  if (gt < 16 * 128 * 8) reinterpret_cast<uint4*>(&g_stats[0][0][0])[gt] = sent;
  if (gt < 6 * 2 * 16 * 8) reinterpret_cast<uint4*>(&g_cnt[0][0][0][0])[gt] = make_uint4(0, 0, 0, 0);
}

namespace C {
constexpr int OFF_WK = 0;
constexpr int OFF_WO = 81920;
constexpr int OFF_WXQ = 131072;
constexpr int OFF_WXV = 133120;
constexpr int STAGE_Q = 51200, STAGE_V = 133120;
constexpr int OFF_R = 139264;
constexpr int OFF_OG = OFF_R + 16384;
constexpr int OFF_RING = 180224;
constexpr int OFF_SCR = OFF_RING + 49152;
constexpr int SLOT = 6144;
__host__ __device__ constexpr int slot_off(int c) { return c < 3 ? OFF_R + 22528 + c * SLOT : c < 6 ? OFF_RING + (c - 3) * SLOT : OFF_RING + 20480 + (c - 6) * SLOT; }
constexpr int OFF_QT = OFF_RING;
constexpr int OFF_KT = OFF_RING + 10240;
constexpr int OFF_VT = OFF_RING + 20480;
constexpr int OFF_P = OFF_RING + 30720;
constexpr int OFF_XL = OFF_P + 7680;
constexpr int OFF_XM = OFF_XL + 10752;
__host__ __device__ constexpr int xl_off(int w) { return OFF_XL + (w ? w * 1152 - 512 : 0); }
constexpr int OFF_BAR = 231424;
constexpr int OFF_TS = OFF_BAR + 256;
constexpr int SMEM = 232448;
constexpr uint32_t SB0 = 1024;
constexpr int BAR_F0 = OFF_BAR, BAR_F1 = OFF_BAR + 8, BAR_F2 = OFF_BAR + 16,
              BAR_W1 = OFF_BAR + 80, BAR_W2 = OFF_BAR + 88, BAR_W3 = OFF_BAR + 96, BAR_X = OFF_BAR + 32,
              BAR_OG2 = OFF_BAR + 104, BAR_XE = OFF_BAR + 112,
              BAR_OG = OFF_BAR + 120, BAR_OE = OFF_BAR + 128, BAR_ROT = OFF_BAR + 136, BAR_RQ = OFF_BAR + 168, BAR_VF = OFF_BAR + 144, BAR_RF = OFF_BAR + 152,
              BAR_RE = OFF_BAR + 160, BAR_RID = OFF_BAR + 24, BAR_M = OFF_BAR + 176,
              OFF_SEL = OFF_BAR + 224;
constexpr int NB_M = 1, NB_QK = 2, NB_P = 3, NB_V = 4, NB_MR = 5, NB_GO = 6, NB_O = 7, NB_BQ = 8, NB_BV = 9, NB_S = 10, NB_X = 11, NB_M2 = 15;
#define B1 300
#define B2 400
#define B3 1500
#define OSP 0
#define PL2 1
#define PL1 1
#define OGF 1
#define PFD 3
constexpr float SCL = 0.07216878364870322f * 1.4426950408889634f;
__host__ __device__ constexpr int wo_off(int u) { return u < 2 ? OFF_RING + u * 8192 : u < 8 ? OFF_WO + (u - 2) * 8192 : OFF_R + (u - 8) * 8192; }
}

struct ChainArgs {
  const uint8_t* xn;
  uint8_t* oimg;
  uint8_t* mbuf;
  uint8_t* mail;
  uint8_t* rot;
  int ten;
  uint64_t td[40], rd[40], kd[44], od[40], gd[12], sd[16], vd[5], pd[12];
};

template <int NK>
__device__ __forceinline__ void load_wfrags(uint32_t (&a)[NK][4], uint32_t base, int w, int lane) {
  const int i = lane >> 3, r = lane & 7;
  const int chunk = 2 * w + (i & 1);
  const uint32_t a0 = base + (r + (i >> 1) * 8) * 128 + ((chunk ^ r) << 4);
#pragma unroll
  for (int k = 0; k < NK; k++) ldsm4t(a[k], a0 + k * 2048);
}
__device__ __forceinline__ uint64_t desc2(uint32_t lo, uint32_t hi) { uint64_t d; asm("mov.b64 %0,{%1,%2};" : "=l"(d) : "r"(lo), "r"(hi)); return d; }
__host__ __device__ __forceinline__ constexpr uint64_t wdesc(int off) { return mkdesc(C::SB0 + off, 8192, 1024); }
__host__ __device__ __forceinline__ constexpr uint64_t rdesc(int k) { return mkdesc_ns(C::SB0 + C::OFF_R + k * 256, 128, 10240); }
__host__ __device__ __forceinline__ constexpr uint64_t tdesc(int k) { return mkdesc_ns(C::SB0 + C::slot_off(k >> 2) + (k & 3) * 256, 128, 1024); }
template <int N>
__device__ __forceinline__ void store_pair(const float (&d)[N], int j0, int j1, uint32_t a) {
  stsm4(a, pack_bf16(d[4 * j0], d[4 * j0 + 1]), pack_bf16(d[4 * j0 + 2], d[4 * j0 + 3]), pack_bf16(d[4 * j1], d[4 * j1 + 1]), pack_bf16(d[4 * j1 + 2], d[4 * j1 + 3]));
}
__device__ __forceinline__ uint32_t tile_lane(int tid) { return (((tid >> 4) & 6) + ((tid >> 3) & 1)) * 1280 + (tid & 7) * 16; }
__device__ __forceinline__ void load_chunk(const CUtensorMap& tmX, uint32_t sb, int b, int c, int off, int bar) {
  tma3d_mc(sb + off, &tmX, c * 256, 4 * b, 0, sb + bar);
}
__device__ __forceinline__ void arrive_all(uint32_t sb, int bar, int i) {
  asm volatile("{.reg .pred p; .reg .b32 a; setp.lt.u32 p,%1,3; @p mapa.shared::cluster.u32 a,%0,%1; @p mbarrier.arrive.shared::cluster.b64 _,[a];}"
               ::"r"(sb + bar), "r"(i) : "memory");
}
static void fill_descs(ChainArgs& a) {
  using namespace C;
  for (int k = 0; k < 40; k++) a.td[k] = tdesc(k);
  for (int k = 0; k < 40; k++) { a.rd[k] = rdesc(k); a.kd[k] = wdesc(OFF_WK + k * 2048); a.od[k] = wdesc(wo_off(k >> 2) + (k & 3) * 2048); }
  for (int k = 0; k < 4; k++) a.kd[40 + k] = wdesc(OFF_WXQ + k * 2048);
  for (int k = 0; k < 12; k++) a.gd[k] = mkdesc_ns(SB0 + OFF_OG + k * 512, 256, 128);
  for (int k = 0; k < 8; k++) {
    a.sd[2 * k] = mkdesc_ns(SB0 + OFF_QT + (k >> 1) * 2560 + (k & 1) * 256, 1280, 128);
    a.sd[2 * k + 1] = mkdesc_ns(SB0 + OFF_KT + (k >> 1) * 2560 + (k & 1) * 640, 1280, 128);
  }
  for (int k = 0; k < 5; k++) a.vd[k] = mkdesc_ns(SB0 + OFF_VT + k * 256, 128, 1280);
  const int grp[4] = {0, 9, 1, 5};
  for (int k = 0; k < 12; k++) a.pd[k] = mkdesc_ns(SB0 + OFF_P + grp[k / 3] * 768 + (k % 3) * 256, 128, 768);
}

#define B1T 2
#define RIDL 0
#define ORING 63
#define S9E 1
#define F2K 16
#define PVE 0
#define QGA 3
#define NOX 0
#define VD 0
#define TD(k) a.td[k]
#define RD(k) a.rd[k]
template <int N, typename F>
__device__ __forceinline__ void k_chunk(F mma, float (&d)[N], uint32_t alo, uint32_t blo, uint32_t bhi) {
  wg_fence();
#pragma unroll
  for (int k = 0; k < 4; k++) mma(d, desc2(alo + k * 128, (uint32_t)(wdesc(0) >> 32)), desc2(blo + k * 16, bhi), 1);
  wg_commit();
}

__device__ __forceinline__ uint32_t quad_max_h2(uint32_t m) {
  const uint32_t a = __shfl_xor_sync(0xffffffffu, m, 1), b = __shfl_xor_sync(0xffffffffu, m, 2), c = __shfl_xor_sync(0xffffffffu, m, 3);
  return max_h2(max_h2(m, a), max_h2(b, c));
}
__device__ __forceinline__ uint32_t diag_mask(int lane) {
  const int dg = (lane >> 2) - 2 * (lane & 3);
  return dg >= 1 ? 0u : dg == 0 ? 0xFC000000u : 0xFC00FC00u;
}
__device__ __forceinline__ float quad_sum(float m) {
  const float a = __shfl_xor_sync(0xffffffffu, m, 1), b = __shfl_xor_sync(0xffffffffu, m, 2), c = __shfl_xor_sync(0xffffffffu, m, 3);
  return (m + a) + (b + c);
}
__device__ __forceinline__ float rcp(float x) { float y; asm("rcp.approx.ftz.f32 %0,%1;" : "=f"(y) : "f"(x)); return y; }
__device__ __forceinline__ void p_store(uint32_t base, bool layer, int lane, uint32_t p0, uint32_t p1, uint32_t p2, uint32_t p3, uint32_t p4) {
  stsm4(base + (layer ? 128 : 0) + lane * 16, p0, p1, p2, p3);
  stsm2(base + ((lane & 8) ? (layer ? 0 : 640) : (layer ? 640 : 512)) + (lane & 7) * 16, p4, 0u);
}

__device__ __forceinline__ void chain_q(const CUtensorMap& tmWk, const CUtensorMap& tmWo, const CUtensorMap& tmX, const ChainArgs& a,
                                        const uint32_t sb, const int tid0, const int cta, const int rank) {
  using namespace C;
  asm volatile("setmaxnreg.inc.sync.aligned.u32 208;");
  int left = SPIN_BUDGET;
  uint32_t wf[39][4];
  mbar_wait(sb + BAR_W1, 0, left);
  PTS(4);
  load_wfrags<39>(wf, sb + STAGE_Q, tid0 >> 5, tid0 & 31);
  cluster_sync();
  PTS(5);
  const uint32_t qa = sb + OFF_QT + tile_lane(tid0) + ((tid0 & 16) ? 9 * 128 : 0);
  const int dq = (tid0 & 16) ? -128 : 128;
  const int warp = __shfl_sync(0xffffffffu, tid0 >> 5, 0);
  if (tid0 < 4) mbar_expect_tx(sb + BAR_F0 + 8 * tid0, tid0 == 3 ? 20480 : (3 + (tid0 >> 1)) * SLOT);
  if (tid0 == 0) {
    const int head = cta / 3, col = head * DH + rank * 64;
    mbar_expect_tx(sb + BAR_W2, 32768);
    for (int i = 6; i < 10; i++) tma2d(sb + OFF_WK + i * 8192, &tmWk, col, i * 64, sb + BAR_W2);
    load_chunk(tmX, sb, 0, rank, slot_off(rank), BAR_F0);
    mbar_expect_tx(sb + BAR_W3, 81920);
    for (int u = 9; u >= 0; u--) {
      const int n = u ? (u - 1) / 3 : 0;
      tma2d(sb + wo_off(u), &tmWo, u == 0 ? 576 : (3 * rank + (u - 1) % 3) * 64, head * DH + ((rank + 3 - n) % 3) * 64, sb + BAR_W3);
    }
  }
  __syncwarp();

  for (int b = 0; b < NS; b++) {
    const int ph = b & 1;
    {
      float d[24];
      mbar_wait(sb + BAR_F0, ph, left);
      if (b > 0) bar_sync(NB_GO, 256);
      TSB(b, 16);
      wg_fence();
#pragma unroll
      for (int k = 0; k < 12; k++) wgmma_rs48(d, wf[k], TD(k), k);
      wg_commit();
      mbar_wait(sb + BAR_F1, ph, left);
      wg_fence();
#pragma unroll
      for (int k = 12; k < F2K; k++) wgmma_rs48(d, wf[k], TD(k), 1);
      wg_commit();
      wg_wait<1>();
      arrive_all(sb, BAR_RE, tid0 - 32);
      if (warp == 0) {
        mbar_wait(sb + BAR_VF, ph, left);
        if (elect()) {
          load_chunk(tmX, sb, b, 6 + rank, slot_off(6) + rank * SLOT, BAR_F2);
          if (rank == 0) load_chunk(tmX, sb, b, 9, slot_off(9), BAR_F2);
        }
        TS(b, 21);
      }
      wg_fence();
#pragma unroll
      for (int k = F2K; k < 24; k++) wgmma_rs48(d, wf[k], TD(k), 1);
      if (RIDL == 0 && warp == 0 && rank) {
        mbar_wait(sb + BAR_RE, ph, left);
        if (elect()) bulk_g2s_mc(sb + OFF_R + (1 + rank) * 10240, a.xn + (size_t)(4 * b + 3 + (rank - 1) * (256 - 4 * LAG)) * 10240, 10240, sb + BAR_RID);
      }
      mbar_wait(sb + BAR_F2, ph, left);
      if (RIDL == 1 && warp == 0 && rank) {
        mbar_wait(sb + BAR_RE, ph, left);
        if (elect()) bulk_g2s_mc(sb + OFF_R + (1 + rank) * 10240, a.xn + (size_t)(4 * b + 3 + (rank - 1) * (256 - 4 * LAG)) * 10240, 10240, sb + BAR_RID);
      }
      wg_fence();
#pragma unroll
      for (int k = 24; k < 39; k++) wgmma_rs48(d, wf[k], TD(k), 1);
      wgmma_ts48(d, a.kd[40], TD(39), 1);
      wg_commit();
      wg_wait<0>();
      TS(b, 17);
      bar_arrive(NB_BQ, 256);
      arrive_all(sb, BAR_XE, tid0 - 32);
      bar_sync(NB_BV, 256);
#pragma unroll
      for (int j = 0; j < 3; j++) store_pair(d, j, j + 3, qa + (4 - j) * dq);
    }
    {
      float d[16];
      bar_sync(NB_M2, 256);
      TSB(b, 18);
      wg_fence();
#pragma unroll
      for (int k = 0; k < 39; k++) wgmma_rs32(d, wf[k], RD(k), k);
      wgmma_ts32(d, a.kd[40], RD(39), 1);
      wg_commit();
      wg_wait<0>();
      TS(b, 19);
      store_pair(d, 0, 1, qa);
      store_pair(d, 2, 3, qa + dq);
      fence_async();
      bar_arrive(NB_QK, 384);
    }
    const int bn = b + 1;
    if (tid0 < 4) mbar_expect_tx(sb + BAR_F0 + 8 * tid0, tid0 == 3 ? 20480 : (3 + (tid0 >> 1)) * SLOT);
    {
      const int lane = fresh(tid0) & 31;
      const bool up = warp >= 2, outer = warp == 0 || warp == 3;
      const uint32_t xo = xl_off(warp), ob = sb + xo + lane * 16;
      const uint32_t dm = diag_mask(lane);
      if (warp == 0) {
        bar_sync(NB_S, 288);
        if (bn < NS && elect()) {
          mbar_expect_tx(sb + BAR_ROT, 16384);
          bulk_g2s(sb + wo_off(0), a.rot + (size_t)cta * 32768, 16384, sb + BAR_ROT);
        }
        __syncwarp();
      }
      bar_sync(NB_X + warp, 64);
      fence_async();
      if (elect()) {
        const uint32_t r1 = mapa(sb, (rank + 1) % 3), r2 = mapa(sb, (rank + 2) % 3), n = outer ? 640 : 1152;
        bulk_s2c(r1 + xo + 3584, sb + xo + 7168, n, r1 + BAR_X + 8 + 8 * warp);
        bulk_s2c(r2 + xo, sb + xo + 7168, n, r2 + BAR_X + 8 + 8 * warp);
      }
      __syncwarp();
      mbar_wait(sb + BAR_X + 8 + 8 * warp, ph, left);
      {
        float z[10];
        const uint4 s = lds128(ob + 7168), u = lds128(ob), v = lds128(ob + 3584);
        const uint32_t ts = lds32(ob + 7168 + 512 - lane * 12), tu = lds32(ob + 512 - lane * 12), tv = lds32(ob + 3584 + 512 - lane * 12);
        const uint32_t h[5] = {add_h2(add_h2(s.x, u.x), v.x), add_h2(add_h2(s.y, u.y), v.y), add_h2(add_h2(add_h2(s.z, outer ? 0u : dm), u.z), v.z),
                               add_h2(add_h2(s.w, u.w), v.w), add_h2(add_h2(add_h2(ts, dm), tu), tv)};
        const uint32_t ma = max_h2(max_h2(h[0], h[1]), h[2]), mb = max_h2(h[3], h[4]);
        uint32_t m = max_h2(__byte_perm(ma, mb, 0x5410), __byte_perm(ma, mb, 0x7632));
        if (outer) m = max_h2(m, __byte_perm(m, m, 0x1032));
        const float2 mf = unpack_h2(quad_max_h2(m));
        const float m0 = -SCL * mf.x, m1 = -SCL * mf.y;
#pragma unroll
        for (int j = 0; j < 5; j++) {
          const float2 f = unpack_h2(h[j]);
          z[2 * j] = ex2(fmaf(f.x, SCL, j < 3 ? m0 : m1)); z[2 * j + 1] = ex2(fmaf(f.y, SCL, j < 3 ? m0 : m1));
        }
        float s0 = ((z[0] + z[1]) + (z[2] + z[3])) + (z[4] + z[5]), s1 = (z[6] + z[7]) + (z[8] + z[9]);
        if (outer) s0 = s1 = s0 + s1;
        s0 += __shfl_xor_sync(0xffffffffu, s0, 1); s1 += __shfl_xor_sync(0xffffffffu, s1, 1);
        s0 = rcp(s0 + __shfl_xor_sync(0xffffffffu, s0, 2)); s1 = rcp(s1 + __shfl_xor_sync(0xffffffffu, s1, 2));
        const uint32_t p3 = pack_bf16(z[6] * s1, z[7] * s1), p4 = pack_bf16(z[8] * s1, z[9] * s1);
        p_store(sb + OFF_P + (2 * warp + (up ? 2 : 1)) * 768, up, lane, pack_bf16(z[0] * s0, z[1] * s0), pack_bf16(z[2] * s0, z[3] * s0), pack_bf16(z[4] * s0, z[5] * s0),
                outer ? p3 : 0u, outer ? p4 : 0u);
        if (!outer) p_store(sb + OFF_P + (up ? 4 * 768 : 5 * 768), !up, lane, p3, p4, 0u, 0u, 0u);
      }
      fence_async();
      bar_arrive(NB_V, 384);
      TS(b, 31);
    }
  }
  if (left <= 0) g_err = 1;
}

__device__ __forceinline__ void chain_v(const ChainArgs& a, const uint32_t sb, const int tid0, const int cta, const int rank) {
  using namespace C;
  asm volatile("setmaxnreg.inc.sync.aligned.u32 224;");
  int left = SPIN_BUDGET;
  uint32_t wf[37][4];
  mbar_wait(sb + BAR_W1, 0, left);
  load_wfrags<37>(wf, sb + STAGE_V + 3 * 2048, tid0 >> 5, tid0 & 31);
  cluster_sync();
  mbar_wait(sb + BAR_W2, 0, left);
  uint32_t mo = (24 * rank + (tid0 >> 4)) * MAIL_UNIT + (cta / 24) * 8192 + ((cta / 3) & 7) * 256 + (tid0 & 15) * 16;
  const int blk9 = cta / 24 + (cta % 24 < 16 ? 0 : 4);
  uint32_t mo9 = (72 + (tid0 >> 3)) * MAIL_UNIT + blk9 * 8192 + ((cta % 24) & 15) * 128 + (tid0 & 7) * 16;
#pragma unroll 1
  for (int i = 0; i < 4; i++) {
    const uint32_t* p = &g_sel[i < 3 ? 24 * rank + 8 * i + (tid0 >> 4) : 72 + (tid0 >> 3)];
    uint32_t v;
    while (__any_sync(0xffffffffu, (v = ld_acquire(p)) == 0) && (left -= 16) > 0) {}
    v = (v >> (i < 3 ? cta / 24 : blk9)) & 1;
    if (i == 0) mo |= v * 0x1003;
    else if (i < 3) mo ^= v * i;
    else mo9 |= v << 12;
  }
  const uint32_t ka = sb + OFF_KT + tile_lane(tid0) + ((tid0 & 16) ? 640 : 0);
  const int warp = __shfl_sync(0xffffffffu, tid0 >> 5, 0);

  for (int b = 0; b < NS; b++) {
    const int ph = b & 1;
    {
      float dv[24], dk[24];
#define VK(K0, K1)                                                   \
  wg_fence();                                                        \
  _Pragma("unroll") for (int k = K0; k < K1; k++) {                  \
    if (k < 3) wgmma_ts48(dv, a.kd[41 + k], TD(k), k);               \
    else wgmma_rs48(dv, wf[k - 3], TD(k), 1);                        \
    wgmma_ts48(dk, a.kd[k], TD(k), k);                               \
  }                                                                  \
  wg_commit();
      mbar_wait(sb + BAR_F0, ph, left);
      TSB(b, 22);
      VK(0, 12)
      mbar_wait(sb + BAR_F1, ph, left);
      VK(12, 15)
      wg_wait<1>();
      arrive_all(sb, BAR_RE, tid0);
      VK(15, 24)
      TS(b, 23);
      mbar_wait(sb + BAR_F2, ph, left);
      VK(24, 27)
      wg_wait<1>();
      bar_arrive(NB_BV, 256);
      VK(27, 40)
#undef VK
      wg_wait<0>();
      TS(b, 24);
      arrive_all(sb, BAR_XE, tid0);
      bar_sync(NB_BQ, 256);
#pragma unroll
      for (int j = 0; j < 3; j++) { store_pair(dk, j, j + 3, ka + (1 + j) * 128); store_pair(dv, j, j + 3, ka + 10240 + (1 + j) * 128); }
    }
    const bool succ = b + 1 < NS;
    {
      float d[16] = {};
      bar_sync(NB_M, 256);
#pragma unroll 1
      for (int c = 0; c < a.ten; c++) k_chunk(wgmma_ts32, d, (uint32_t)wdesc(OFF_WK) + c * 512, (uint32_t)rdesc(0) + c * 64, (uint32_t)(rdesc(0) >> 32));
      wg_wait<0>();
      TS(b, 25);
      store_pair(d, 0, 1, ka);
      store_pair(d, 2, 3, ka + 4 * 128);
      fence_async();
      bar_arrive(NB_QK, 384);
      bar_sync(NB_S, 288);
      wg_fence();
#pragma unroll
      for (int k = 0; k < 40; k++) {
        if (k < 3) wgmma_ts32(d, a.kd[41 + k], RD(k), k);
        else wgmma_rs32(d, wf[k - 3], RD(k), 1);
      }
      wg_commit();
      wg_wait<0>();
      TS(b, 26);
      arrive_all(sb, BAR_OE, tid0 - 32);
      if (warp == 0 && succ && elect()) {
        mbar_expect_tx(sb + BAR_OG, 2048);
        mbar_expect_tx(sb + BAR_OG2, 16384 + 2048);
        bulk_g2s(sb + wo_off(8), a.rot + (size_t)cta * 32768 + 16384, 16384, sb + BAR_OG2);
      }
      __syncwarp();
      store_pair(d, 0, 1, ka + 10240);
      store_pair(d, 2, 3, ka + 10240 + 4 * 128);
      fence_async();
      if (!succ) { bar_arrive(NB_V, 384); break; }
      mbar_wait(sb + BAR_ROT, ph, left);
    }
    bar_sync(NB_P, 192);
    TSB(b, 27);
    {
      float o0[4], o1[4];
      wg_fence();
#pragma unroll
      for (int q = 0; q < 3; q++) {
        wgmma_ss8(o0, a.vd[q], a.pd[q], q);
        wgmma_ss8(o1, a.vd[2 + q], a.pd[3 + q], q);
      }
      wg_commit();
      wg_wait<0>();
      TS(b, 6);
      stsm4(sb + OFF_OG + tid0 * 16, pack_bf16(o0[0], o0[1]), pack_bf16(o1[0], o1[1]), pack_bf16(o0[2], o0[3]), pack_bf16(o1[2], o1[3]));
      fence_async();
    }
    bar_sync(NB_O, 160);
    TSB(b, 7);
    {
      float acc[4][8];
      wg_fence();
#pragma unroll
      for (int kk = 0; kk < 4; kk++) wgmma_tt16(acc[3], a.od[kk], a.gd[kk], kk);
#pragma unroll
      for (int i = 0; i < 3; i++)
#pragma unroll
        for (int kk = 0; kk < 4; kk++) {
          wgmma_tt16(acc[i], a.od[4 + 4 * i + kk], a.gd[kk], kk);
          if (i != 1 && kk == 3) wg_commit();
        }
      wg_wait<1>();
      arrive_all(sb, BAR_RQ, tid0);
      uint8_t* mb = a.mail + ph * 2048;
      const uint32_t tag = (b >> 1) & 1, radd = tag ? 0u : 0x10000u;
#define TAGPACK(LO, HI) (__byte_perm(((__float_as_uint(LO) + radd) & 0xFFFE0000u) | (tag << 16), pack_bf16(0.f, HI), 0x7632))
#define SEND(O, I) st_msg16(mb + (O), TAGPACK(acc[I][0], acc[I][2]), pack_bf16(acc[I][1], acc[I][3]), \
                            pack_bf16(acc[I][4], acc[I][6]), pack_bf16(acc[I][5], acc[I][7]))
      if (S9E == 1) { SEND(mo9, 3); __syncwarp(); }
      mbar_wait(sb + BAR_OG, ph, left);
      if (S9E == 2) { SEND(mo9, 3); __syncwarp(); }
      TS(b, 8);
      wg_fence();
#pragma unroll
      for (int k = 0; k < 12; k++) wgmma_tt16(acc[k >> 2], a.od[16 + k], a.gd[4 + (k & 3)], 1);
      mbar_wait(sb + BAR_OG2, ph, left);
      TS(b, 29);
      wg_fence();
#pragma unroll
      for (int k = 0; k < 12; k++) {
        wgmma_tt16(acc[k >> 2], a.od[28 + k], a.gd[8 + (k & 3)], 1);
        if ((k & 3) == 3) wg_commit();
      }
      const uint32_t o = mo & ~3u;
      if (!S9E) { SEND(mo9, 3); __syncwarp(); }
      wg_wait<2>();
      SEND(o, 0);
      __syncwarp();
      wg_wait<1>();
      SEND((o ^ ((mo & 1) << 12)) + 8 * MAIL_UNIT, 1);
      __syncwarp();
      if (QGA == 2) bar_arrive(NB_GO, 256);
      wg_wait<0>();
      if (QGA == 3) bar_arrive(NB_GO, 256);
      TS(b, 30);
      if (PVE) bar_arrive(NB_V, 384);
      SEND((o ^ ((mo & 2) << 11)) + 16 * MAIL_UNIT, 2);
      if (!PVE) bar_arrive(NB_V, 384);
      if (QGA == 0) bar_arrive(NB_GO, 256);
#undef SEND
#undef TAGPACK
      TS(b, 9);
      arrive_all(sb, BAR_RF, tid0 - 96);
      if (VD) { const uint32_t t0 = clk32(); while (clk32() - t0 < VD) {} }
    }
  }
  if (left <= 0) g_err = 2;
}

__device__ __forceinline__ void sum_msg(float (&e)[8], const uint4& a, const uint4& b, const uint4& c, const uint4& d) {
  e[0] = (bf_lo(a.x) + bf_lo(b.x)) + (bf_lo(c.x) + bf_lo(d.x)); e[1] = (bf_hi(a.x) + bf_hi(b.x)) + (bf_hi(c.x) + bf_hi(d.x));
  e[2] = (bf_lo(a.y) + bf_lo(b.y)) + (bf_lo(c.y) + bf_lo(d.y)); e[3] = (bf_hi(a.y) + bf_hi(b.y)) + (bf_hi(c.y) + bf_hi(d.y));
  e[4] = (bf_lo(a.z) + bf_lo(b.z)) + (bf_lo(c.z) + bf_lo(d.z)); e[5] = (bf_hi(a.z) + bf_hi(b.z)) + (bf_hi(c.z) + bf_hi(d.z));
  e[6] = (bf_lo(a.w) + bf_lo(b.w)) + (bf_lo(c.w) + bf_lo(d.w)); e[7] = (bf_hi(a.w) + bf_hi(b.w)) + (bf_hi(c.w) + bf_hi(d.w));
}
__device__ __forceinline__ void publish(const ChainArgs& a, int b, int warp, uint32_t src, uint32_t o) {
  const uint32_t off = (o >> 12) * 8192 + (o & 4095);
  uint32_t v = SENT;
  if (warp < 2) {
    const uint2 p = lds64(src), q = lds64(src + 256), r = lds64(src + 512), s = lds64(src + 768);
    v = pack_bf16((__uint_as_float(p.x) + __uint_as_float(q.x)) + (__uint_as_float(r.x) + __uint_as_float(s.x)),
                  (__uint_as_float(p.y) + __uint_as_float(q.y)) + (__uint_as_float(r.y) + __uint_as_float(s.y)));
    if (b + 1 == LAG && o >= 10240) v = ld_relaxed(a.mbuf + 2 * 40960 + off);
  }
  uint8_t* dst = a.mbuf + (((b + 1 + (warp >> 1)) & 1) * 40960 + off);
  st_relaxed(dst, v);
  st_relaxed(dst + 4096, v);
}

__device__ __forceinline__ void store_o(const ChainArgs& a, const uint4 (&ok)[4], int b, int cta, int tid) {
  uint8_t* p0 = a.oimg + (uint32_t)((((b >> 1) & ORING) * 96 + cta) * 8192 + (b & 1) * 512 + (tid >> 5) * 2048 + ((tid ^ ((tid >> 3) & 3)) & 31) * 16);
  static_assert(LAG % 2 == 0, "both segments sit in the same half of their row block");
  if (b < NSEG) { *reinterpret_cast<uint4*>(p0) = ok[0]; *reinterpret_cast<uint4*>(p0 + 1024) = ok[1]; }
  p0 += (size_t)((NSEG - LAG) / 2) * 96 * 8192;
  if (b >= LAG) { *reinterpret_cast<uint4*>(p0) = ok[2]; *reinterpret_cast<uint4*>(p0 + 1024) = ok[3]; }
}

__device__ __forceinline__ void fetch_rows(const ChainArgs& a, uint32_t sb, int warp, int slot, uint32_t al) {
  using namespace C;
  const uint8_t* src = a.mbuf + slot * 40960;
  mbar_expect_tx(sb + BAR_M + 8 * warp, 5120);
  bulk_g2s(sb + OFF_R + warp * 4096, src + (warp * 8192 + ((al >> warp) & 1) * 4096), 4096, sb + BAR_M + 8 * warp);
  bulk_g2s(sb + OFF_R + 16384 + warp * 1024, src + (32768 + (al & 16) * 256 + warp * 1024), 1024, sb + BAR_M + 8 * warp);
}

__device__ __forceinline__ void chain_a(const CUtensorMap& tmX, const ChainArgs& a, const uint32_t sb, const int tid0, const int cta, const int rank, const int unit) {
  using namespace C;
  asm volatile("setmaxnreg.dec.sync.aligned.u32 72;");
  int left = SPIN_BUDGET;
  const int warp = __shfl_sync(0xffffffffu, tid0 >> 5, 0);
  uint32_t rsel;
  asm volatile("ld.shared.u8 %0,[%1];" : "=r"(rsel) : "r"(sb + OFF_SEL + (tid0 & 31)) : "memory");
  rsel = __ballot_sync(0xffffffffu, rsel) & 0x3ffff;
  if (unit < NUNIT) {
#pragma unroll 1
    for (int i = tid0; i < (unit < 72 ? 1024 : 2048); i += 128)
      *reinterpret_cast<uint4*>(a.mail + (size_t)unit * MAIL_UNIT + (i >> 8) * 8192 + ((rsel >> (10 + (i >> 8))) & 1) * 4096 + (i & 255) * 16) = make_uint4(SENT, SENT, SENT, SENT);
    bar_sync(NB_MR, 128);
    if (tid0 == 0) asm volatile("st.release.gpu.global.b32 [%0],%1;" ::"l"(&g_sel[unit]), "r"(256 | (rsel >> 10)) : "memory");
  }
  cluster_sync();
  mbar_wait(sb + BAR_W3, 0, left);
  PTS(6);
#pragma unroll 1
  for (int it = 2559 - tid0; it >= 0; it -= 128) {
    const int row = it >> 2, q = it & 3;
    const uint32_t base = sb + (row < 384 ? OFF_WO : row < 512 ? wo_off(0) - 6 * 8192 : wo_off(8) - 8 * 8192) + row * 128;
    const uint32_t a0 = base + (((2 * q) ^ (row & 7)) << 4), a1 = base + (((2 * q + 1) ^ (row & 7)) << 4);
    const uint4 u = lds128(a0), v = lds128(a1);
    sts128(a0, make_uint4(__byte_perm(u.x, u.y, 0x5410), __byte_perm(u.z, u.w, 0x5410), __byte_perm(v.x, v.y, 0x5410), __byte_perm(v.z, v.w, 0x5410)));
    sts128(a1, make_uint4(__byte_perm(u.x, u.y, 0x7632), __byte_perm(u.z, u.w, 0x7632), __byte_perm(v.x, v.y, 0x7632), __byte_perm(v.z, v.w, 0x7632)));
    if (row >= 384 && row < 416) {
      fence_async();
      bar_sync(NB_MR, 128);
      if (tid0 == 0) {
        bulk_s2g(a.rot + (size_t)cta * 32768, sb + wo_off(0), 16384);
        bulk_s2g(a.rot + (size_t)cta * 32768 + 16384, sb + wo_off(8), 16384);
        bulk_commit();
      }
    }
  }
  fence_async();
  if (tid0 == 0) bulk_wait();
  bar_sync(NB_MR, 128);
  arrive_all(sb, BAR_RF, tid0);
  arrive_all(sb, BAR_VF, tid0);
  __syncwarp();
  mbar_wait(sb + BAR_RF, 0, left);
  if (tid0 == 0) load_chunk(tmX, sb, 0, 3 + rank, slot_off(3) + rank * SLOT, BAR_F1);
  __syncwarp();
  uint4 ok[4] = {};
  uint32_t mph = 0;
  uint32_t mo = (unit < NUNIT ? unit : NUNIT) * MAIL_UNIT + warp * 8192 + ((rsel >> (10 + warp)) & 1) * 4096 + (tid0 & 31) * 16;
  const uint32_t mo2 = 32768 + (((rsel >> (10 + warp)) ^ (rsel >> (14 + warp))) & 1) * 4096;
  DUR(1);
  __syncwarp();
  if (elect()) fetch_rows(a, sb, warp, 2, 0);
  __syncwarp();

  for (int b = 0; b < NS; b++) {
    const int ph = b & 1;
    {
      const int lane = fresh(tid0) & 31;
      const uint32_t va = sb + OFF_R + lane * 32 + (lane & 28);
      int n = 0;
      if (OSP == 1 && b > 0) store_o(a, ok, b - 1, cta, fresh(tid0));
      mbar_wait(sb + BAR_RID, ph, left);
#pragma unroll 1
      while (true) {
        mbar_wait(sb + BAR_M + 8 * warp, mph, left);
        if (n == 0) TS(b, 13);
        const uint32_t v0 = lds32(va + warp * 4096), v1 = lds32(va + warp * 4096 + 1024), v2 = lds32(va + warp * 4096 + 2048), v3 = lds32(va + warp * 4096 + 3072);
        const uint32_t v4 = lds32(va + 16384 + warp * 1024), v5 = lds32((va ^ 8) + (warp == 2 ? 9216 : 16384 + warp * 1024));
        mph ^= 1;
        n++;
        if (!__any_sync(0xffffffffu, max(max(max(v0, v1), v2), max(max(v3, v4), v5)) == SENT) || (left -= 16) <= 0) break;
        if (elect()) fetch_rows(a, sb, warp, ph, rsel >> (5 * ph));
        __syncwarp();
      }
      bar_arrive(NB_M, 256);
      bar_arrive(NB_M2, 256);
      TS(b, 0);
      TSV(b, 14, n);
    }
    if (b > 0) {
      if (OSP == 0) store_o(a, ok, b - 1, cta, fresh(tid0));
      static_assert(LAG % 4 == 2, "one batch at a time");
      const int l = (b >> 1) & 1, s = b - 1 - l * LAG;
      if (!(b & 1) && s >= 0 && s < NSEG) {
        bar_sync(NB_MR, 128);
        if (warp == 1 && elect()) cnt_signal(CN_O, l, s >> 2);
      }
    }
    if (tid0 < 5) mbar_expect_tx(sb + BAR_X + 8 * tid0, tid0 == 0 ? 2560 : (tid0 & 2) ? 2304 : 1280);
    if ((tid0 & 31) == 8) mbar_expect_tx(sb + BAR_M + 8 * warp, 5120);
    TS_FLUSH(b - 1);
    mbar_wait(sb + BAR_XE, ph, left);
    {
      const int lane = fresh(tid0) & 31, w = fresh(warp);
      const bool up = w >= 2, outer = w == 0 || w == 3;
      const uint32_t r1 = mapa(sb, (rank + 1) % 3), r2 = mapa(sb, (rank + 2) % 3);
      const uint32_t pa = OFF_P + (2 * w + (up ? 3 : 0)) * 768;
      const uint32_t ob = xl_off(w) + lane * 16;
      const uint32_t oa = outer ? pa + lane * 16 : ob + 640, oc = outer ? OFF_XM + (up ? 640 : 0) + lane * 16 : ob + 640 + 3584;
      float x0[20], x1[20];
      bar_sync(NB_QK, 384);
      TSB(b, 1);
      wg_fence();
#pragma unroll
      for (int kk = 0; kk < 4; kk++) {
        wgmma_tt40(x0, a.sd[4 * kk], a.sd[4 * kk + 1], kk);
        wgmma_tt40(x1, a.sd[4 * kk + 2], a.sd[4 * kk + 3], kk);
      }
      wg_commit();
      wg_wait<0>();
      bar_arrive(NB_S, 288);
      TS(b, 2);
      uint32_t h[5], z[5];
#pragma unroll
      for (int j = 0; j < 5; j++) h[j] = pack_h2(up ? x1[4 * j + 2] : x0[4 * j], up ? x1[4 * j + 3] : x0[4 * j + 1]);
      if (outer) {
        st_async4(r1 + oc, h[0], h[1], h[2], h[3], r1 + BAR_X);
        st_async4(r2 + oa, h[0], h[1], h[2], h[3], r2 + BAR_X);
        st_async1(r1 + oc + 512 - lane * 12, h[4], r1 + BAR_X);
        st_async1(r2 + oa + 512 - lane * 12, h[4], r2 + BAR_X);
      } else {
        sts128(sb + oa + 7168, make_uint4(h[0], h[1], h[2], h[3]));
      }
#pragma unroll
      for (int j = 0; j < 5; j++) z[j] = pack_h2(up ? x1[4 * j] : x0[4 * j + 2], up ? x1[4 * j + 1] : x0[4 * j + 3]);
      if (!outer) {
#pragma unroll
        for (int j = 0; j < 2; j++) z[3 + j] = pack_h2(up ? x0[4 * j] : x1[4 * j + 2], up ? x0[4 * j + 1] : x1[4 * j + 3]);
        h[3] = add_h2(h[3], diag_mask(lane));
      }
      sts128(sb + ob + 7168, make_uint4(z[0], z[1], z[2], z[3]));
      sts32(sb + ob + 7168 + 512 - lane * 12, z[4]);
      bar_arrive(NB_X + w, 64);
      TS(b, 3);
      mbar_wait(sb + BAR_X + (outer ? 0 : 8 + 8 * w), ph, left);
      TS(b, 4);
      {
        const uint4 u = lds128(sb + oa), v = lds128(sb + oc);
        const uint32_t tu = lds32(sb + oa + 512 - lane * 12), tv = lds32(sb + oc + 512 - lane * 12);
        h[0] = add_h2(add_h2(h[0], u.x), v.x); h[1] = add_h2(add_h2(h[1], u.y), v.y); h[2] = add_h2(add_h2(h[2], u.z), v.z);
        h[3] = add_h2(add_h2(h[3], u.w), v.w); h[4] = outer ? add_h2(add_h2(h[4], tu), tv) : 0xFC00FC00u;
        const float2 mf = unpack_h2(quad_max_h2(max_h2(max_h2(max_h2(h[0], h[1]), max_h2(h[2], h[3])), h[4])));
        const float m = -SCL * fmaxf(mf.x, mf.y);
        float y[10];
#pragma unroll
        for (int j = 0; j < 5; j++) { const float2 f = unpack_h2(h[j]); y[2 * j] = ex2(fmaf(f.x, SCL, m)); y[2 * j + 1] = ex2(fmaf(f.y, SCL, m)); }
        const float r = rcp(quad_sum(((y[0] + y[1]) + (y[2] + y[3])) + ((y[4] + y[5]) + (y[6] + y[7])) + (y[8] + y[9])));
        p_store(sb + pa, up, lane, pack_bf16(y[0] * r, y[1] * r), pack_bf16(y[2] * r, y[3] * r), pack_bf16(y[4] * r, y[5] * r),
                pack_bf16(y[6] * r, y[7] * r), pack_bf16(y[8] * r, y[9] * r));
      }
      fence_async();
      if (outer) bar_arrive(NB_P, 192);
      TS(b, 5);
    }
    const int bn = b + 1;
    if (warp == 0 && bn < NS) {
      if (!NOX && bn >= LAG && ((bn - LAG) & 3) == 0) {
        while (__any_sync(0xffffffffu, ld_acquire(cnt_ptr(CN_X, 0, (bn - LAG) >> 2)) < 5) && (left -= 16) > 0) {}
        fence_async_all();
      }
      mbar_wait(sb + BAR_OE, ph, left);
      if (elect()) load_chunk(tmX, sb, bn, rank, slot_off(0) + rank * SLOT, BAR_F0);
      TS(b, 20);
      mbar_wait(sb + BAR_RQ, ph, left);
      if (elect()) load_chunk(tmX, sb, bn, 3 + rank, slot_off(3) + rank * SLOT, BAR_F1);
      __syncwarp();
    }
    if (warp == 3 && bn < NS) {
      const uint32_t r1 = mapa(sb, (rank + 1) % 3), r2 = mapa(sb, (rank + 2) % 3);
      mbar_wait(sb + BAR_OE, ph, left);
      bar_sync(NB_O, 160);
      if (elect()) {
        bulk_s2c(r1 + OFF_OG + 2048, sb + OFF_OG, 2048, r1 + BAR_OG);
        bulk_s2c(r2 + OFF_OG + 4096, sb + OFF_OG, 2048, r2 + BAR_OG2);
      }
      __syncwarp();
    }
    uint4 x[6];
    bar_sync(NB_V, 384);
    {
      float o0[16], o1[16];
      wg_fence();
#pragma unroll
      for (int q = 0; q < 3; q++) {
        wgmma_ss32(o0, a.vd[q], a.pd[6 + q], q);
        wgmma_ss32(o1, a.vd[2 + q], a.pd[9 + q], q);
      }
      wg_commit();
      if (bn < NS) {
        if (unit < 72) mbar_wait(sb + BAR_RF, ph ^ 1, left);
        if (QGA == 1) bar_arrive(NB_GO, 256);
        if (B1 && unit < 72 && (unit >> 3) % 3 >= B1T) { const uint32_t t0 = clk32(); while (clk32() - t0 < B1) {} }
      }
      ld_msg16x4(x, a.mail + mo);
      __syncwarp();
      wg_wait<0>();
      arrive_all(sb, BAR_VF, tid0);
#pragma unroll
      for (int h = 0; h < 2; h++) {
        ok[h] = make_uint4(pack_bf16(o0[12 + 2 * h], o0[13 + 2 * h]), pack_bf16(o0[8 + 2 * h], o0[9 + 2 * h]),
                           pack_bf16(o0[4 + 2 * h], o0[5 + 2 * h]), pack_bf16(o0[2 * h], o0[1 + 2 * h]));
        ok[2 + h] = make_uint4(pack_bf16(o1[2 * h], o1[1 + 2 * h]), pack_bf16(o1[4 + 2 * h], o1[5 + 2 * h]),
                               pack_bf16(o1[8 + 2 * h], o1[9 + 2 * h]), pack_bf16(o1[12 + 2 * h], o1[13 + 2 * h]));
      }
      TS(b, 28);
    }
    if (b + 1 == NS) break;
    {
      const int lane = fresh(tid0) & 31;
      const uint32_t tag = (b >> 1) & 1;
      int n = 1;
      float e[8];
      if (unit < 72) {
#pragma unroll 1
        while (true) {
          const bool bad = __any_sync(0xffffffffu, differ4(x[0].x, x[1].x, x[2].x, x[3].x, tag) & 1);
          sum_msg(e, x[0], x[1], x[2], x[3]);
          if (!bad || (left -= 16) <= 0) break;
          ld_msg16x4(x, a.mail + mo);
          n++;
        }
        TS(b, 10);
        TSV(b, 15, n);
        float f[4];
        const bool b4 = lane & 16;
#pragma unroll
        for (int i = 0; i < 4; i++) f[i] = (b4 ? e[4 + i] : e[i]) + __shfl_xor_sync(0xffffffffu, b4 ? e[i] : e[4 + i], 16);
        sts128(sb + OFF_SCR + (lane & 16) * 64 + warp * 256 + (lane & 15) * 16, make_uint4(__float_as_uint(f[0]), __float_as_uint(f[1]), __float_as_uint(f[2]), __float_as_uint(f[3])));
        bar_sync(NB_MR, 128);
        publish(a, b, warp, sb + OFF_SCR + warp * 1024 + (lane & 3) * 64 + (lane >> 2) * 8, (warp & 1) * 10240 + unit * 128 + lane * 4);
      } else if (unit < NUNIT) {
        ld_msg16x2(x + 4, a.mail + (mo ^ mo2));
        __syncwarp();
#pragma unroll 1
        while (true) {
          const bool bad = __any_sync(0xffffffffu, (differ4(x[0].x, x[1].x, x[2].x, x[3].x, tag) | differ4(x[4].x, x[5].x, x[4].x, x[5].x, tag)) & 1);
          sum_msg(e, x[0], x[1], x[2], x[3]);
          e[0] += bf_lo(x[4].x) + bf_lo(x[5].x); e[1] += bf_hi(x[4].x) + bf_hi(x[5].x); e[2] += bf_lo(x[4].y) + bf_lo(x[5].y); e[3] += bf_hi(x[4].y) + bf_hi(x[5].y);
          e[4] += bf_lo(x[4].z) + bf_lo(x[5].z); e[5] += bf_hi(x[4].z) + bf_hi(x[5].z); e[6] += bf_lo(x[4].w) + bf_lo(x[5].w); e[7] += bf_hi(x[4].w) + bf_hi(x[5].w);
          if (!bad || (left -= 16) <= 0) break;
          ld_msg16x6(x, a.mail + mo, a.mail + (mo ^ mo2));
          n++;
        }
        TS(b, 10);
        TSV(b, 15, n);
        float f[4];
        const bool b4 = lane & 16, b3 = lane & 8;
#pragma unroll
        for (int i = 0; i < 4; i++) f[i] = (b4 ? e[4 + i] : e[i]) + __shfl_xor_sync(0xffffffffu, b4 ? e[i] : e[4 + i], 16);
        const float h0 = (b3 ? f[2] : f[0]) + __shfl_xor_sync(0xffffffffu, b3 ? f[0] : f[2], 8);
        const float h1 = (b3 ? f[3] : f[1]) + __shfl_xor_sync(0xffffffffu, b3 ? f[1] : f[3], 8);
        asm volatile("st.shared.v2.f32 [%0],{%1,%2};" ::"r"(sb + OFF_SCR + warp * 256 + lane * 8), "f"(h0), "f"(h1) : "memory");
        bar_sync(NB_MR, 128);
        if (!(warp & 1))
          publish(a, b, warp, sb + OFF_SCR + lane * 8, (lane >> 4) * 10240 + (36 + (unit >> 1)) * 128 + (lane & 3) * 32 + (lane & 8) * 2 + (unit & 1) * 8 + (lane & 4));
      }
      const uint32_t t0 = clk32();
      mo ^= 2048;
      TS(b, 11);
      if (rank < 2) {
        const int q = 2 * rank + (warp >> 1), blk = (warp & 1) ? 4 : q, o = blk * 4096 + ((warp & 1) ? q * 1024 : 0);
        const uint8_t* src = a.mbuf + (uint32_t)((ph ^ 1) * 40960 + o + (blk + ((rsel >> (5 - 5 * ph + blk)) & 1)) * 4096);
        while (clk32() - t0 < B2) {}
        if (elect()) bulk_g2s_mc(sb + OFF_R + o, src, (warp & 1) ? 1024 : 4096, sb + BAR_M + 8 * q);
        __syncwarp();
      }
      TS(b + 1, 12);
    }
  }
  store_o(a, ok, NS - 1, cta, tid0);
  bar_sync(NB_MR, 128);
  if (tid0 == 0) cnt_signal(CN_O, 1, 15);
  TS_FLUSH(NS - 1);
  if (left <= 0) g_err = 3;
}

__global__ void __cluster_dims__(3, 1, 1) __launch_bounds__(384, 1)
k_chain(const __grid_constant__ CUtensorMap tmWq, const __grid_constant__ CUtensorMap tmWk, const __grid_constant__ CUtensorMap tmWv,
        const __grid_constant__ CUtensorMap tmWo, const __grid_constant__ CUtensorMap tmX, const __grid_constant__ ChainArgs args) {
  using namespace C;
  extern __shared__ __align__(1024) uint8_t smem[];
  const uint32_t sb = smem_u32(smem);
  const int tid = threadIdx.x;
  const int wg = __shfl_sync(0xffffffffu, tid >> 7, 0);
  const int cta = blockIdx.x, rank = cta % 3;
  DUR(0);
  asm volatile("griddepcontrol.launch_dependents;");
  if (tid == 0) {
    if ((sb & 0xFFFFFF) != SB0) g_err = 100;
    for (int i = 0; i < 3; i++) mbar_init(sb + BAR_F0 + 8 * i, 1);
    mbar_init(sb + BAR_W1, 1); mbar_init(sb + BAR_W2, 1); mbar_init(sb + BAR_W3, 1);
    for (int i = 0; i < 5; i++) mbar_init(sb + BAR_X + 8 * i, 1);
    mbar_init(sb + BAR_OG2, 1);
    mbar_init(sb + BAR_XE, 6); mbar_init(sb + BAR_OG, 1); mbar_init(sb + BAR_OE, 3);
    mbar_init(sb + BAR_ROT, 1); mbar_init(sb + BAR_RQ, 3); mbar_init(sb + BAR_VF, 3); mbar_init(sb + BAR_RF, 3); mbar_init(sb + BAR_RE, 6);
    mbar_init(sb + BAR_RID, 1);
    for (int i = 0; i < 4; i++) mbar_init(sb + BAR_M + 8 * i, 1);
    asm volatile("fence.mbarrier_init.release.cluster;" ::: "memory");
    fence_async();
    mbar_expect_tx(sb + BAR_W1, 163840 + 6 * 8192);
    const int col = (cta / 3) * DH + rank * 64;
    for (int i = 0; i < 10; i++) {
      tma2d(sb + STAGE_Q + i * 8192, &tmWq, col, i * 64, sb + BAR_W1);
      tma2d(sb + STAGE_V + i * 8192, &tmWv, col, i * 64, sb + BAR_W1);
      if (i < 6) tma2d(sb + OFF_WK + i * 8192, &tmWk, col, i * 64, sb + BAR_W1);
    }
  }
  const int unit = rank < 2 ? (cta / 3) * 2 + rank : 64 + cta / 3;
  if ((tid & 31) == 0) {
#pragma unroll 1
    for (int job = 11 - (tid >> 5); job < 18; job += 12) {
      uint32_t best[2] = {SENT, SENT};
      if (job < (unit < 72 ? 14 : unit < NUNIT ? 18 : 10)) {
        uint8_t* p = job < 10 ? args.mbuf + job * 8192 + cta * 32 : args.mail + (size_t)unit * MAIL_UNIT + (job - 10) * 8192;
#pragma unroll 1
        for (int r = 0; r < 12; r++) {
          const uint32_t t0 = clk32();
          uint32_t v;
          asm volatile("atom.relaxed.gpu.global.exch.b32 %0,[%1],%2;" : "=r"(v) : "l"(p + (r & 1) * 4096), "r"(SENT) : "memory");
          uint32_t dt = t0 - 1;
          asm volatile("{.reg .b64 c; .reg .pred p; setp.eq.b32 p,%1,-1; @p mov.u64 c,%%clock64; @p cvt.u32.u64 %0,c;}" : "+r"(dt) : "r"(v) : "memory");
          dt -= t0;
          if (r & 1) best[1] = min(best[1], dt); else best[0] = min(best[0], dt);
        }
      }
      asm volatile("st.shared.u8 [%0],%1;" ::"r"(sb + OFF_SEL + job), "r"((job < 10 ? PL2 : PL1) && best[1] < best[0] ? 1 : 0) : "memory");
    }
  }
  __syncthreads();

  const int tid0 = __shfl_sync(0xffffffffu, tid & 127, tid & 31);
  if (wg == 0) chain_a(tmX, args, sb, tid0, cta, rank, unit);
  else if (wg == 1) chain_q(tmWk, tmWo, tmX, args, sb, tid0, cta, rank);
  else chain_v(args, sb, tid0, cta, rank);
  DUR(2);
  cluster_sync();
}

#define OHK 7
#define IMMREL 7
#define HOIST 2
#define SIGF 1
#define LN30 1
__device__ __forceinline__ void mbar_wait_div(uint32_t bar, uint32_t ph, int& left) {
  if (mbar_try(bar, ph)) return;
  while (!mbar_try(bar, ph) && --left > 0) {}
}
namespace W {
constexpr int NW = 36;
constexpr int NP = 30;
constexpr int OW0 = 31;
constexpr int PST = 3, PSTAGE = 32768;
constexpr int BST = 3, BSTAGE = 16384;
constexpr int OFF_P = 0;
constexpr int OFF_WQ = OFF_P + PST * PSTAGE;
constexpr int OFF_B = OFF_WQ + 81920;
constexpr int OFF_HIST = OFF_B + BST * BSTAGE;
constexpr int OFF_BAR = OFF_HIST + 2 * 14 * 80;
constexpr int SMEM = OFF_BAR + 128;
constexpr int BAR_PF = OFF_BAR, BAR_PE = OFF_BAR + 24, BAR_BF = OFF_BAR + 48, BAR_BE = OFF_BAR + 72;
constexpr int PITCH = 136;
constexpr int NB_P = 1, NB_B = 2;
}

struct WorkArgs {
  const bf16* res[2];
  bf16* xa[2];
  bf16* xb[2];
  const bf16* wqkv;
};

#define FOR_BATCHES(l, b)                                  \
  for (int j_ = 0; j_ < 2 * NS; j_++) {                    \
    const int l = j_ & 1, s_ = (j_ >> 1) - l * LAG;        \
    if (s_ < 0 || s_ >= NSEG || (s_ & 3) != 3) continue;   \
    const int b = s_ >> 2;

template <bool IS_O>
__device__ __forceinline__ void work_gemm_producer(const CUtensorMap& tm, const WorkArgs& a, uint32_t sb, int w) {
  using namespace W;
  constexpr int KCH = IS_O ? 10 : 96, NK = IS_O ? 10 : 16;
  int dead = SPIN_BUDGET, st = 0;
  uint32_t ph = 1;
  const int col = (IS_O ? w - OW0 : w % 5) * 128, k0 = IS_O ? 0 : (w / 5) * 16;
  FOR_BATCHES(l, b)
    const uint8_t* src = (IS_O ? g_ob[l] : g_o[l]) + ((size_t)(2 * b) * KCH + k0) * 8192;
#pragma unroll 1
    for (int kc = 0; kc < NK; kc++) {
      const uint32_t bar = sb + BAR_PF + 8 * st, d = sb + OFF_P + st * PSTAGE;
      mbar_wait_div(sb + BAR_PE + 8 * st, ph, dead);
      mbar_expect_tx(bar, PSTAGE);
      tma2d(d + 16384, &tm, col, (k0 + kc) * 64, bar);
      tma2d(d + 24576, &tm, col + 64, (k0 + kc) * 64, bar);
      if (kc >= PST) {
        bulk_g2s(d, src + (size_t)kc * 8192, 8192, bar);
        bulk_g2s(d + 8192, src + (size_t)(KCH + kc) * 8192, 8192, bar);
      }
      if (++st == PST) { st = 0; ph ^= 1; }
      if (kc == PST - 1) {
        cnt_wait(IS_O ? CN_A : CN_O, l, b, IS_O ? 32 : 96, dead);
        if (!IS_O && w == 0) WTS(l, b, 0);
        if (IS_O && w == 35) WTS(l, b, 3);
        fence_async_all();
#pragma unroll
        for (int i = 0; i < PST; i++) {
          const int s2 = (st + i) % PST;
          bulk_g2s(sb + OFF_P + s2 * PSTAGE, src + (size_t)i * 8192, 8192, sb + BAR_PF + 8 * s2);
          bulk_g2s(sb + OFF_P + s2 * PSTAGE + 8192, src + (size_t)(KCH + i) * 8192, 8192, sb + BAR_PF + 8 * s2);
        }
      }
    }
  }
}

__device__ __forceinline__ void quad_transpose(uint32_t* x, int t) {
  const bool h = t & 2, o = t & 1;
  uint32_t p = __shfl_xor_sync(0xffffffffu, h ? x[0] : x[2], 2), q = __shfl_xor_sync(0xffffffffu, h ? x[1] : x[3], 2);
  const uint32_t y0 = h ? p : x[0], y1 = h ? q : x[1], y2 = h ? x[2] : p, y3 = h ? x[3] : q;
  p = __shfl_xor_sync(0xffffffffu, o ? y0 : y1, 1); q = __shfl_xor_sync(0xffffffffu, o ? y2 : y3, 1);
  x[0] = o ? p : y0; x[1] = o ? y1 : p; x[2] = o ? q : y2; x[3] = o ? y3 : q;
}

template <bool IS_O>
__device__ __forceinline__ void work_gemm(const WorkArgs& a, uint32_t sb, int w, int tid0) {
  using namespace W;
  constexpr int NK = IS_O ? 10 : 16;
  int dead = SPIN_BUDGET, st = 0;
  uint32_t ph = 0;
  const int tile = IS_O ? w - OW0 : w % 5;
  bool first = true;
  FOR_BATCHES(l, b)
    float acc[64];
    uint32_t r0[16], r1[16];
    int prev = 0;
    if (IS_O) {
#pragma unroll
      for (int i = 0; i < 64; i++) acc[i] = 0.f;
    }
#pragma unroll 1
    for (int kc = 0; kc < NK; kc++) {
      mbar_wait_div(sb + BAR_PF + 8 * st, ph, dead);
      if (w == (IS_O ? 35 : WW) && tid0 == 0 && kc == 0) WTS(l, b, IS_O ? 16 : 5);
      const uint32_t pa = sb + OFF_P + st * PSTAGE + (tid0 >> 7) * 8192, pb = sb + OFF_P + st * PSTAGE + 16384;
      wg_fence();
#pragma unroll
      for (int kk = 0; kk < 4; kk++) {
        if (IS_O) wgmma_st128(acc, mkdesc(pa + kk * 32, 16, 1024), mkdesc(pb + kk * 2048, 8192, 1024), (kc | kk) != 0);
        else wgmma_tt128(acc, mkdesc64(pa + kk * 2048, 512, 1024), mkdesc(pb + kk * 2048, 8192, 1024), (kc | kk) != 0);
      }
      wg_commit();
      if (IS_O && OHK >= 0 && kc == OHK) {
      const int tid = fresh(tid0), g = (tid & 31) >> 2, t = tid & 3;
      const bf16* rp = a.xa[l] + (size_t)(b * 128 + (tid >> 5) * 16 + g) * DM + tile * 128 + 8 * t;
#pragma unroll
      for (int m = 0; m < 4; m++) {
        const float4 c0 = ld_relaxed4f(rp + 32 * m), c1 = ld_relaxed4f(rp + 8 * DM + 32 * m);
        r0[4 * m] = __float_as_uint(c0.x); r0[4 * m + 1] = __float_as_uint(c0.y); r0[4 * m + 2] = __float_as_uint(c0.z); r0[4 * m + 3] = __float_as_uint(c0.w);
        r1[4 * m] = __float_as_uint(c1.x); r1[4 * m + 1] = __float_as_uint(c1.y); r1[4 * m + 2] = __float_as_uint(c1.z); r1[4 * m + 3] = __float_as_uint(c1.w);
      }
      }
      if (IMMREL & (IS_O ? 2 : 1)) {
        if (kc < NK - 1) {
          wg_wait<0>();
          if ((tid0 & 127) == 0) mbar_arrive(sb + BAR_PE + 8 * st);
        }
      } else if (kc > 0) {
        wg_wait<1>();
        if ((tid0 & 127) == 0) mbar_arrive(sb + BAR_PE + 8 * prev);
      }
      prev = st;
      if (++st == PST) { st = 0; ph ^= 1; }
    }
    if (IS_O && OHK < 0) {
      const int tid = fresh(tid0), g = (tid & 31) >> 2, t = tid & 3;
      const bf16* rp = a.xa[l] + (size_t)(b * 128 + (tid >> 5) * 16 + g) * DM + tile * 128 + 8 * t;
#pragma unroll
      for (int m = 0; m < 4; m++) {
        const float4 c0 = ld_relaxed4f(rp + 32 * m), c1 = ld_relaxed4f(rp + 8 * DM + 32 * m);
        r0[4 * m] = __float_as_uint(c0.x); r0[4 * m + 1] = __float_as_uint(c0.y); r0[4 * m + 2] = __float_as_uint(c0.z); r0[4 * m + 3] = __float_as_uint(c0.w);
        r1[4 * m] = __float_as_uint(c1.x); r1[4 * m + 1] = __float_as_uint(c1.y); r1[4 * m + 2] = __float_as_uint(c1.z); r1[4 * m + 3] = __float_as_uint(c1.w);
      }
    }
    wg_wait<0>();
    if ((tid0 & 127) == 0) mbar_arrive(sb + BAR_PE + 8 * prev);
    if (w == (IS_O ? 35 : WW) && tid0 == 0) WTS(l, b, IS_O ? 17 : 6);
    if (!IS_O) {
      if (first) {
        if ((tid0 & 31) == 0) cnt_wait(CN_Z, 0, 0, NW, dead);
        __syncwarp();
        first = false;
      }
      const int tid = fresh(tid0);
      float* dst = &g_acc[l][b][tile][0] + (tid >> 5) * 2048 + (tid & 31) * 4;
#pragma unroll
      for (int i = 0; i < 16; i++)
        asm volatile("red.relaxed.gpu.global.add.v4.f32 [%0],{%1,%2,%3,%4};" ::"l"(dst + i * 128), "f"(acc[4 * i]), "f"(acc[4 * i + 1]), "f"(acc[4 * i + 2]), "f"(acc[4 * i + 3]) : "memory");
      if (w == WW && tid0 == 0) WTS(l, b, 7);
      bar_sync(NB_P, 256);
      if (tid0 == 0) cnt_signal(CN_P, l, b);
      if (w == WW && tid0 == 0) WTS(l, b, 8);
    } else {
      const int tid = fresh(tid0), g = (tid & 31) >> 2, t = tid & 3;
      const int rb = (tid >> 5) * 16 + g, R0 = b * 128 + rb;
      float s0 = 0.f, s1 = 0.f;
      bf16* xp = a.xb[l] + (size_t)R0 * DM + tile * 128 + 8 * t;
      uint32_t c0[16], c1[16];
#pragma unroll
      for (int j = 0; j < 16; j++) { c0[j] = pack_bf16(acc[4 * j], acc[4 * j + 1]); c1[j] = pack_bf16(acc[4 * j + 2], acc[4 * j + 3]); }
#pragma unroll
      for (int m = 0; m < 4; m++) { quad_transpose(c0 + 4 * m, t); quad_transpose(c1 + 4 * m, t); }
#pragma unroll
      for (int j = 0; j < 16; j++) {
        const uint32_t u0 = c0[j], u1 = c1[j];
        const uint32_t y0 = pack_bf16(bf_lo(r0[j]) + bf_lo(u0), bf_hi(r0[j]) + bf_hi(u0));
        const uint32_t y1 = pack_bf16(bf_lo(r1[j]) + bf_lo(u1), bf_hi(r1[j]) + bf_hi(u1));
        acc[4 * j] = bf_lo(y0); acc[4 * j + 1] = bf_hi(y0); acc[4 * j + 2] = bf_lo(y1); acc[4 * j + 3] = bf_hi(y1);
        s0 += acc[4 * j] + acc[4 * j + 1]; s1 += acc[4 * j + 2] + acc[4 * j + 3];
      }
      if (l == 0) {
        s0 += __shfl_xor_sync(0xffffffffu, s0, 1); s1 += __shfl_xor_sync(0xffffffffu, s1, 1);
        s0 += __shfl_xor_sync(0xffffffffu, s0, 2); s1 += __shfl_xor_sync(0xffffffffu, s1, 2);
        const float tm0 = s0 * (1.f / 128), tm1 = s1 * (1.f / 128);
        float q0 = 0.f, q1 = 0.f;
#pragma unroll
        for (int j = 0; j < 16; j++) {
          const float a0 = acc[4 * j] - tm0, b0 = acc[4 * j + 1] - tm0, a1 = acc[4 * j + 2] - tm1, b1 = acc[4 * j + 3] - tm1;
          q0 += a0 * a0 + b0 * b0; q1 += a1 * a1 + b1 * b1;
        }
        q0 += __shfl_xor_sync(0xffffffffu, q0, 1); q1 += __shfl_xor_sync(0xffffffffu, q1, 1);
        q0 += __shfl_xor_sync(0xffffffffu, q0, 2); q1 += __shfl_xor_sync(0xffffffffu, q1, 2);
        float2* sp = &g_stats[b][rb][0];
        if (t < 2) {
          const float sx = t ? s1 : s0, qx = t ? q1 : q0;
          asm volatile("st.relaxed.gpu.global.v2.f32 [%0],{%1,%2};" ::"l"(sp + t * 8 * 16 + tile), "f"(sx), "f"(qx) : "memory");
        }
#pragma unroll
        for (int m = 0; m < 4; m++) {
          const float* c = acc + 16 * m;
          *reinterpret_cast<uint4*>(xp + 32 * m) = make_uint4(pack_bf16(c[0], c[1]), pack_bf16(c[4], c[5]), pack_bf16(c[8], c[9]), pack_bf16(c[12], c[13]));
          *reinterpret_cast<uint4*>(xp + 8 * DM + 32 * m) = make_uint4(pack_bf16(c[2], c[3]), pack_bf16(c[6], c[7]), pack_bf16(c[10], c[11]), pack_bf16(c[14], c[15]));
        }
        if (w == 35 && tid0 == 0) WTS(l, b, 18);
        float2 e0[2], e1[2];
                while (true) {
          e0[0] = ld_relaxed2f(sp + t); e1[0] = ld_relaxed2f(sp + 8 * 16 + t);
          e0[1] = ld_relaxed2f(sp + 4); e1[1] = ld_relaxed2f(sp + 8 * 16 + 4);
          bool bad = false;
#pragma unroll
          for (int i = 0; i < 2; i++)
            bad |= __float_as_uint(e0[i].x) == SENT || __float_as_uint(e0[i].y) == SENT || __float_as_uint(e1[i].x) == SENT || __float_as_uint(e1[i].y) == SENT;
          if (!__any_sync(0xffffffffu, bad && (dead -= 16) > 0)) break;
        }
        if (w == 35 && tid0 == 0) WTS(l, b, 19);
        float m0 = e0[0].x, m1 = e1[0].x;
        m0 += __shfl_xor_sync(0xffffffffu, m0, 1); m1 += __shfl_xor_sync(0xffffffffu, m1, 1);
        m0 += __shfl_xor_sync(0xffffffffu, m0, 2); m1 += __shfl_xor_sync(0xffffffffu, m1, 2);
        m0 = (m0 + e0[1].x) * (1.f / DM); m1 = (m1 + e1[1].x) * (1.f / DM);
        const float d0 = e0[0].x * (1.f / 128) - m0, d1 = e1[0].x * (1.f / 128) - m1;
        float v0 = e0[0].y + 128.f * d0 * d0, v1 = e1[0].y + 128.f * d1 * d1;
        v0 += __shfl_xor_sync(0xffffffffu, v0, 1); v1 += __shfl_xor_sync(0xffffffffu, v1, 1);
        v0 += __shfl_xor_sync(0xffffffffu, v0, 2); v1 += __shfl_xor_sync(0xffffffffu, v1, 2);
        const float d2 = e0[1].x * (1.f / 128) - m0, d3 = e1[1].x * (1.f / 128) - m1;
        v0 += e0[1].y + 128.f * d2 * d2; v1 += e1[1].y + 128.f * d3 * d3;
        const float rs0 = rsqrtf(v0 * (1.f / DM) + 1e-5f), rs1 = rsqrtf(v1 * (1.f / DM) + 1e-5f);
        uint8_t* img = g_xn[1] + (size_t)(R0 >> 3) * 10240 + tile * 2048 + g * 16 + t * 128;
#pragma unroll
        for (int m = 0; m < 4; m++) {
          uint8_t* o = img + m * 512;
          const float* c = acc + 16 * m;
          *reinterpret_cast<uint4*>(o) = make_uint4(pack_bf16((c[0] - m0) * rs0, (c[1] - m0) * rs0), pack_bf16((c[4] - m0) * rs0, (c[5] - m0) * rs0),
                                                    pack_bf16((c[8] - m0) * rs0, (c[9] - m0) * rs0), pack_bf16((c[12] - m0) * rs0, (c[13] - m0) * rs0));
          *reinterpret_cast<uint4*>(o + 10240) = make_uint4(pack_bf16((c[2] - m1) * rs1, (c[3] - m1) * rs1), pack_bf16((c[6] - m1) * rs1, (c[7] - m1) * rs1),
                                                            pack_bf16((c[10] - m1) * rs1, (c[11] - m1) * rs1), pack_bf16((c[14] - m1) * rs1, (c[15] - m1) * rs1));
        }
        bar_sync(NB_P, 256);
        if (tid0 == 0) { fence_async_all(); cnt_signal(CN_X, 0, b); }
      } else {
#pragma unroll
        for (int m = 0; m < 4; m++) {
          const float* c = acc + 16 * m;
          *reinterpret_cast<uint4*>(xp + 32 * m) = make_uint4(pack_bf16(c[0], c[1]), pack_bf16(c[4], c[5]), pack_bf16(c[8], c[9]), pack_bf16(c[12], c[13]));
          *reinterpret_cast<uint4*>(xp + 8 * DM + 32 * m) = make_uint4(pack_bf16(c[2], c[3]), pack_bf16(c[6], c[7]), pack_bf16(c[10], c[11]), pack_bf16(c[14], c[15]));
        }
      }
      if (w == 35 && tid0 == 0) { WTS(l, b, 4); WTS(l, b, 20); }
    }
  }
}

__device__ __forceinline__ void work_q_producer(const WorkArgs& a, uint32_t sb) {
  using namespace W;
  int dead = SPIN_BUDGET, st = 0;
  uint32_t ph = 1;
  FOR_BATCHES(l, b)
    cnt_wait(CN_L, l, b, 64, dead);
    if (blockIdx.x == 0) WTS(l, b, 2);
    fence_async_all();
    const uint8_t* src = g_xnb[l] + (size_t)(2 * b) * 10 * 8192;
#pragma unroll 1
    for (int kc = 0; kc < 10; kc++) {
      const uint32_t bar = sb + BAR_BF + 8 * st, d = sb + OFF_B + st * BSTAGE;
      mbar_wait_div(sb + BAR_BE + 8 * st, ph, dead);
      mbar_expect_tx(bar, BSTAGE);
      bulk_g2s(d, src + (size_t)kc * 8192, 8192, bar);
      bulk_g2s(d + 8192, src + (size_t)(10 + kc) * 8192, 8192, bar);
      if (++st == BST) { st = 0; ph ^= 1; }
    }
  }
}

__device__ __forceinline__ int ln_row(int p) { return (p >> 4) * 32 + ((p >> 1) & 3) * 8 + ((p >> 3) & 1) * 4 + (p & 1); }
__device__ __forceinline__ void work_ln(const WorkArgs& a, int w, int wr, int lane0) {
  int dead = SPIN_BUDGET;
  FOR_BATCHES(l, b)
    uint32_t r0[10], r1[10];
    {
      const int i = (2 * w + wr) * 32 + lane0, st = (j_ >> 1) + 6;
      if (i < 1280) { if (st + i / 320 < NSEG) prefetch_l2(g_xn[0] + (size_t)st * 40960 + i * 128); }
    }
    if (HOIST & 2) {
      if (l == 1) {
        if (lane0 == 0) cnt_wait(CN_X, 0, b, 5, dead);
        __syncwarp();
      }
      const int lane = fresh(lane0), p = 2 * w + wr;
      const bf16* rp = a.res[l] + (size_t)(b * 128 + ln_row(p)) * DM + (lane >> 2) * 8 + 2 * (lane & 3);
#pragma unroll
      for (int i = 0; i < 10; i++) { r0[i] = ld_relaxed(rp + i * 64); r1[i] = ld_relaxed(rp + i * 64 + 2 * DM); }
    }
    if (lane0 == 0) cnt_wait(CN_P, l, b, W::NP, dead);
    __syncwarp();
    if (w == WW && wr == 0 && lane0 == 0) { WTS(l, b, 1); WTS(l, b, 9); }
    const int lane = fresh(lane0), p = 2 * w + wr;
    const int slab = p >> 3, g = p & 7, jj = lane >> 2, t = lane & 3;
    const int R0 = b * 128 + ln_row(p);
    const float* acc = &g_acc[l][b][0][0] + slab * 2048 + (g * 4 + t) * 4 + jj * 128;
    const bf16* rp = a.res[l] + (size_t)R0 * DM + jj * 8 + 2 * t;
    float4 v[10];
#pragma unroll
    for (int i = 0; i < 10; i++) {
      v[i] = ld_relaxed4f(acc + (i >> 1) * 16384 + (i & 1) * 1024);
      if (!(HOIST & 2)) { r0[i] = ld_relaxed(rp + i * 64); r1[i] = ld_relaxed(rp + i * 64 + 2 * DM); }
    }
    float s0 = 0.f, s1 = 0.f;
    bf16* xp = a.xa[l] + (size_t)R0 * DM + jj * 8 + 2 * t;
#pragma unroll
    for (int i = 0; i < 10; i++) {
      const uint32_t u0 = pack_bf16(v[i].x, v[i].y), u1 = pack_bf16(v[i].z, v[i].w);
      r0[i] = pack_bf16(bf_lo(r0[i]) + bf_lo(u0), bf_hi(r0[i]) + bf_hi(u0));
      r1[i] = pack_bf16(bf_lo(r1[i]) + bf_lo(u1), bf_hi(r1[i]) + bf_hi(u1));
      s0 += bf_lo(r0[i]) + bf_hi(r0[i]); s1 += bf_lo(r1[i]) + bf_hi(r1[i]);
    }
#pragma unroll
    for (int o = 16; o > 0; o >>= 1) { s0 += __shfl_xor_sync(0xffffffffu, s0, o); s1 += __shfl_xor_sync(0xffffffffu, s1, o); }
    const float m0 = s0 * (1.f / DM), m1 = s1 * (1.f / DM);
    float q0 = 0.f, q1 = 0.f;
#pragma unroll
    for (int i = 0; i < 10; i++) {
      const float a0 = bf_lo(r0[i]) - m0, b0 = bf_hi(r0[i]) - m0, a1 = bf_lo(r1[i]) - m1, b1 = bf_hi(r1[i]) - m1;
      q0 += a0 * a0 + b0 * b0; q1 += a1 * a1 + b1 * b1;
    }
#pragma unroll
    for (int o = 16; o > 0; o >>= 1) { q0 += __shfl_xor_sync(0xffffffffu, q0, o); q1 += __shfl_xor_sync(0xffffffffu, q1, o); }
    const float rs0 = rsqrtf(q0 * (1.f / DM) + 1e-5f), rs1 = rsqrtf(q1 * (1.f / DM) + 1e-5f);
    uint8_t* img = g_xnb[l] + (size_t)(R0 >> 6) * 10 * 8192 + (R0 & 63) * 128 + t * 4 + ((jj ^ (R0 & 7)) << 4);
    uint8_t* img1 = g_xnb[l] + (size_t)(R0 >> 6) * 10 * 8192 + ((R0 + 2) & 63) * 128 + t * 4 + ((jj ^ ((R0 + 2) & 7)) << 4);
#pragma unroll
    for (int i = 0; i < 10; i++) {
      *reinterpret_cast<uint32_t*>(img + i * 8192) = pack_bf16((bf_lo(r0[i]) - m0) * rs0, (bf_hi(r0[i]) - m0) * rs0);
      *reinterpret_cast<uint32_t*>(img1 + i * 8192) = pack_bf16((bf_lo(r1[i]) - m1) * rs1, (bf_hi(r1[i]) - m1) * rs1);
    }
#pragma unroll
    for (int i = 0; i < 10; i++) {
      *reinterpret_cast<uint32_t*>(xp + i * 64) = r0[i];
      *reinterpret_cast<uint32_t*>(xp + i * 64 + 2 * DM) = r1[i];
    }
    __syncwarp();
    if (w == WW && wr == 0 && lane0 == 0) WTS(l, b, 10);
    if (lane0 == 0) cnt_signal(CN_L, l, b);
    if (w == WW && wr == 0 && lane0 == 0) WTS(l, b, 11);
  }
}

__device__ __forceinline__ void work_q(const WorkArgs& a, uint32_t sb, int w, int tid0) {
  using namespace W;
  int dead = SPIN_BUDGET, st = 0;
  uint32_t ph = 0;
  FOR_BATCHES(l, b)
    {
      float acc0[32], acc1[32];
      int prev = 0;
#pragma unroll 1
      for (int kc = 0; kc < 10; kc++) {
        mbar_wait_div(sb + BAR_BF + 8 * st, ph, dead);
        if (w == WW && tid0 == 0 && kc == 0) WTS(l, b, 12);
        const uint32_t pa = sb + OFF_B + st * BSTAGE, pb = sb + OFF_WQ + kc * 8192;
        wg_fence();
#pragma unroll
        for (int kk = 0; kk < 4; kk++) {
          wgmma_st64(acc0, mkdesc(pa + kk * 32, 16, 1024), mkdesc(pb + kk * 2048, 8192, 1024), (kc | kk) != 0);
          wgmma_st64(acc1, mkdesc(pa + 8192 + kk * 32, 16, 1024), mkdesc(pb + kk * 2048, 8192, 1024), (kc | kk) != 0);
        }
        wg_commit();
        if (IMMREL & 4) {
          if (kc <= 6) {
            wg_wait<0>();
            if (tid0 == 0) mbar_arrive(sb + BAR_BE + 8 * st);
          }
        } else if (kc > 0) {
          wg_wait<1>();
          if (kc <= 7 && tid0 == 0) mbar_arrive(sb + BAR_BE + 8 * prev);
        }
        prev = st;
        if (++st == BST) { st = 0; ph ^= 1; }
      }
      wg_wait<0>();
      bar_sync(NB_B, 128);
      if (w == WW && tid0 == 0) WTS(l, b, 13);
      const int tid = fresh(tid0), wr = tid >> 5, g = (tid & 31) >> 2, t = tid & 3;
      const uint32_t stg = sb + OFF_B, hist = sb + OFF_HIST + l * 1120;
      const uint32_t o = stg + (14 + 16 * wr + g) * PITCH + t * 4;
#pragma unroll
      for (int j = 0; j < 8; j++) {
        sts32(o + j * 16, pack_bf16(acc0[4 * j], acc0[4 * j + 1]));
        sts32(o + 8 * PITCH + j * 16, pack_bf16(acc0[4 * j + 2], acc0[4 * j + 3]));
        sts32(o + 64 * PITCH + j * 16, pack_bf16(acc1[4 * j], acc1[4 * j + 1]));
        sts32(o + 72 * PITCH + j * 16, pack_bf16(acc1[4 * j + 2], acc1[4 * j + 3]));
      }
      for (int i = tid; i < 280; i += 128) {
        uint32_t v; asm volatile("ld.shared.b32 %0,[%1];" : "=r"(v) : "r"(hist + i * 4) : "memory");
        sts32(stg + (i / 20) * PITCH + 40 + (i % 20) * 4, v);
      }
    }
    bar_sync(NB_B, 128);
    {
      const int tid = fresh(tid0);
      const uint32_t stg = sb + OFF_B, hist = sb + OFF_HIST + l * 1120;
      for (int i = tid; i < 280; i += 128) {
        uint32_t v; asm volatile("ld.shared.b32 %0,[%1];" : "=r"(v) : "r"(stg + (128 + i / 20) * PITCH + 40 + (i % 20) * 4) : "memory");
        sts32(hist + i * 4, v);
      }
      const float scl = 0.22360679774997896f * 1.4426950408889634f;
      const uint32_t row = stg + (14 + tid) * PITCH;
      const int pos = b * 128 + tid;
      float q[20];
#pragma unroll
      for (int i = 0; i < 5; i++) {
        uint32_t u0, u1; asm volatile("ld.shared.v2.b32 {%0,%1},[%2];" : "=r"(u0), "=r"(u1) : "r"(row + i * 8) : "memory");
        q[4 * i] = bf_lo(u0); q[4 * i + 1] = bf_hi(u0); q[4 * i + 2] = bf_lo(u1); q[4 * i + 3] = bf_hi(u1);
      }
      float sc[8], mx = -INFINITY;
#pragma unroll
      for (int j = 0; j < 8; j++) {
        float s0 = 0.f, s1 = 0.f;
#pragma unroll
        for (int i = 0; i < 5; i++) {
          uint32_t u0, u1; asm volatile("ld.shared.v2.b32 {%0,%1},[%2];" : "=r"(u0), "=r"(u1) : "r"(row - 2 * j * PITCH + 40 + i * 8) : "memory");
          s0 += q[4 * i] * bf_lo(u0) + q[4 * i + 1] * bf_hi(u0);
          s1 += q[4 * i + 2] * bf_lo(u1) + q[4 * i + 3] * bf_hi(u1);
        }
        sc[j] = pos - 2 * j >= 0 ? (s0 + s1) * scl : -INFINITY;
        mx = fmaxf(mx, sc[j]);
      }
      float sum = 0.f;
#pragma unroll
      for (int j = 0; j < 8; j++) { sc[j] = ex2(sc[j] - mx); sum += sc[j]; }
      const float inv = 1.f / sum;
      float o[20];
#pragma unroll
      for (int i = 0; i < 20; i++) o[i] = 0.f;
#pragma unroll
      for (int j = 0; j < 8; j++) {
        const float pj = __bfloat162float(__float2bfloat16(sc[j] * inv));
#pragma unroll
        for (int i = 0; i < 5; i++) {
          uint32_t u0, u1; asm volatile("ld.shared.v2.b32 {%0,%1},[%2];" : "=r"(u0), "=r"(u1) : "r"(row - 2 * j * PITCH + 80 + i * 8) : "memory");
          o[4 * i] += pj * bf_lo(u0); o[4 * i + 1] += pj * bf_hi(u0); o[4 * i + 2] += pj * bf_lo(u1); o[4 * i + 3] += pj * bf_hi(u1);
        }
      }
      uint8_t* img = g_ob[l] + (size_t)(pos >> 6) * 10 * 8192 + (pos & 63) * 128;
#pragma unroll
      for (int i = 0; i < 5; i++) {
        const int c = w * 20 + 4 * i;
        *reinterpret_cast<uint2*>(img + (c >> 6) * 8192 + ((((c >> 3) & 7) ^ (pos & 7)) << 4) + (c & 7) * 2) =
            make_uint2(pack_bf16(o[4 * i], o[4 * i + 1]), pack_bf16(o[4 * i + 2], o[4 * i + 3]));
      }
    }
    if (w == WW && tid0 == 0) WTS(l, b, 14);
    bar_sync(NB_B, 128);
    if (tid0 == 0) { cnt_signal(CN_A, l, b); if (w == WW) WTS(l, b, 15); }
    fence_async();
    bar_sync(NB_B, 128);
    if (tid0 == 0) for (int i = 0; i < BST; i++) mbar_arrive(sb + BAR_BE + 8 * i);
  }
}

__global__ void __launch_bounds__(512, 1)
k_work(const __grid_constant__ CUtensorMap tmWo, const __grid_constant__ CUtensorMap tmBo, const __grid_constant__ WorkArgs args) {
  using namespace W;
  extern __shared__ __align__(1024) uint8_t smem[];
  const uint32_t sb = smem_u32(smem);
  const int tid = threadIdx.x, w = blockIdx.x;
  const int wg = __shfl_sync(0xffffffffu, tid >> 7, 0);
  if (tid == 0) {
    for (int i = 0; i < PST; i++) { mbar_init(sb + BAR_PF + 8 * i, 1); mbar_init(sb + BAR_PE + 8 * i, 2); }
    for (int i = 0; i < BST; i++) { mbar_init(sb + BAR_BF + 8 * i, 1); mbar_init(sb + BAR_BE + 8 * i, 1); }
    asm volatile("fence.mbarrier_init.release.cluster;" ::: "memory");
  }
  for (int i = w * 512 + tid; i < 2 * 16 * 5 * 4096; i += NW * 512) reinterpret_cast<uint4*>(&g_acc[0][0][0][0])[i] = make_uint4(0, 0, 0, 0);
  if (w < 32) {
    for (int i = tid; i < 640 * 32; i += 512) {
      const int k = i >> 5, c = i & 31;
      uint32_t v = 0;
      if (c < 30) v = *reinterpret_cast<const uint32_t*>(args.wqkv + (size_t)k * 1920 + (c / 10) * 640 + w * 20 + (c % 10) * 2);
      sts32(sb + OFF_WQ + (k >> 6) * 8192 + (k & 63) * 128 + (((c >> 2) ^ (k & 7)) << 4) + (c & 3) * 4, v);
    }
  }
  for (int i = tid; i < 560; i += 512) sts32(sb + OFF_HIST + i * 4, 0);
  fence_async();
  __syncthreads();
  if (tid == 0) cnt_signal(CN_Z, 0, 0);

  if (wg < 2) {
    if (w < NP) work_gemm<false>(args, sb, w, tid);
    else if (w >= OW0) work_gemm<true>(args, sb, w, tid);
    else if (LN30 && tid < 64) work_ln(args, 31, tid >> 5, tid & 31);
  } else if (wg == 2) {
    if (w < 32) work_q(args, sb, w, tid - 256);
  } else if (tid >= 448) {
    if (w < (LN30 ? 31 : 32)) work_ln(args, w, (tid >> 5) & 1, tid & 31);
  } else if (tid == 384) {
    if (w < NP) work_gemm_producer<false>(tmWo, args, sb, w);
    else if (w >= OW0) work_gemm_producer<true>(tmBo, args, sb, w);
  } else if (tid == 416) {
    if (w < 32) work_q_producer(args, sb);
  }
  __syncthreads();
  asm volatile("griddepcontrol.wait;" ::: "memory");
}

typedef CUresult (*EncodeFn)(CUtensorMap*, CUtensorMapDataType, cuuint32_t, void*, const cuuint64_t*, const cuuint64_t*,
                             const cuuint32_t*, const cuuint32_t*, CUtensorMapInterleave, CUtensorMapSwizzle,
                             CUtensorMapL2promotion, CUtensorMapFloatOOBfill);

static void make_map(EncodeFn enc, CUtensorMap* tm, const void* ptr, uint64_t cols, uint64_t rows, uint32_t boxc, uint32_t boxr) {
  cuuint64_t dims[2] = {cols, rows};
  cuuint64_t strides[1] = {cols * 2};
  cuuint32_t box[2] = {boxc, boxr};
  cuuint32_t es[2] = {1, 1};
  enc(tm, CU_TENSOR_MAP_DATA_TYPE_BFLOAT16, 2, const_cast<void*>(ptr), dims, strides, box, es, CU_TENSOR_MAP_INTERLEAVE_NONE,
      CU_TENSOR_MAP_SWIZZLE_128B, CU_TENSOR_MAP_L2_PROMOTION_L2_256B, CU_TENSOR_MAP_FLOAT_OOB_FILL_NONE);
}

extern "C" void kernel_launch(void* const* d_in, const int* in_sizes, int n_in, void* d_out, int out_size) {
  const bf16* x0 = (const bf16*)d_in[0];
  const bf16* mem0 = (const bf16*)d_in[1];
  const bf16* Wq = (const bf16*)d_in[2];
  const bf16* Wk = (const bf16*)d_in[3];
  const bf16* Wv = (const bf16*)d_in[4];
  const bf16* Wo = (const bf16*)d_in[5];
  const bf16* Bqkv = (const bf16*)d_in[8];
  const bf16* Bwo = (const bf16*)d_in[9];
  bf16* out = (bf16*)d_out;

  static EncodeFn enc = nullptr;
  static uint8_t *p_xn, *p_o, *p_mbuf, *p_mail, *p_rot;
  static bf16 *p_x1, *p_x2, *p_x3;
  if (!enc) {
    void* fn = nullptr;
    cudaDriverEntryPointQueryResult qr;
    cudaGetDriverEntryPoint("cuTensorMapEncodeTiled", &fn, cudaEnableDefault, &qr);
    enc = (EncodeFn)fn;
    cudaFuncSetAttribute(k_chain, cudaFuncAttributeMaxDynamicSharedMemorySize, C::SMEM);
    cudaFuncSetAttribute(k_work, cudaFuncAttributeMaxDynamicSharedMemorySize, W::SMEM);
    void* p;
    cudaGetSymbolAddress(&p, g_xn); p_xn = (uint8_t*)p;
    cudaGetSymbolAddress(&p, g_o); p_o = (uint8_t*)p;
    cudaGetSymbolAddress(&p, g_mbuf); p_mbuf = (uint8_t*)p;
    cudaGetSymbolAddress(&p, g_mail); p_mail = (uint8_t*)p;
    cudaGetSymbolAddress(&p, g_rot); p_rot = (uint8_t*)p;
    cudaGetSymbolAddress(&p, g_x1); p_x1 = (bf16*)p;
    cudaGetSymbolAddress(&p, g_x2); p_x2 = (bf16*)p;
    cudaGetSymbolAddress(&p, g_x3); p_x3 = (bf16*)p;
  }
  CUtensorMap tmWq, tmWk, tmWv, tmWo, tmBo, tmX;
  make_map(enc, &tmWq, Wq, NH * DH, DM, 64, 64);
  make_map(enc, &tmWk, Wk, NH * DH, DM, 64, 64);
  make_map(enc, &tmWv, Wv, NH * DH, DM, 64, 64);
  make_map(enc, &tmWo, Wo, DM, NH * DH, 64, 64);
  make_map(enc, &tmBo, Bwo, DM, DM, 64, 64);
  {
    cuuint64_t dims[3] = {2560, 4 * NS, 2};
    cuuint64_t strides[2] = {10240, (cuuint64_t)(256 - 4 * LAG) * 10240};
    cuuint32_t box[3] = {256, 3, 2};
    cuuint32_t es[3] = {1, 1, 1};
    enc(&tmX, CU_TENSOR_MAP_DATA_TYPE_UINT32, 3, p_xn, dims, strides, box, es, CU_TENSOR_MAP_INTERLEAVE_NONE,
        CU_TENSOR_MAP_SWIZZLE_NONE, CU_TENSOR_MAP_L2_PROMOTION_NONE, CU_TENSOR_MAP_FLOAT_OOB_FILL_NONE);
  }

  cudaStream_t st = cudaStreamPerThread;
  k_pre<<<256, 256, 0, st>>>(x0, mem0);
  ChainArgs ca;
  ca.xn = p_xn;
  ca.oimg = p_o;
  ca.mbuf = p_mbuf; ca.mail = p_mail; ca.rot = p_rot;
  ca.ten = 10;
  fill_descs(ca);
  k_chain<<<96, 384, C::SMEM, st>>>(tmWq, tmWk, tmWv, tmWo, tmX, ca);
  WorkArgs wa;
  wa.res[0] = x0; wa.res[1] = p_x2; wa.xa[0] = p_x1; wa.xa[1] = p_x3; wa.xb[0] = p_x2; wa.xb[1] = out;
  wa.wqkv = Bqkv;
  cudaLaunchAttribute at[1];
  at[0].id = cudaLaunchAttributeProgrammaticStreamSerialization; at[0].val.programmaticStreamSerializationAllowed = 1;
  cudaLaunchConfig_t cfg = {};
  cfg.gridDim = dim3(W::NW); cfg.blockDim = dim3(512); cfg.dynamicSmemBytes = W::SMEM; cfg.stream = st;
  cfg.attrs = at; cfg.numAttrs = 1;
  cudaLaunchKernelEx(&cfg, k_work, tmWo, tmBo, wa);
}
```

```cpp
#include <cuda_runtime.h>
#include <cuda_bf16.h>
#include <cuda.h>
#include <stdint.h>

typedef __nv_bfloat16 bf16;

constexpr int SEQ = 2048, DM = 640, NH = 32, DH = 192, NSEG = 64;
#define LAG 6
constexpr int NS = NSEG + LAG;
constexpr uint32_t SENT = 0xFFFFFFFFu;
#define BUDGET_LOG 20
constexpr int SPIN_BUDGET = 1 << BUDGET_LOG;

constexpr int MD = LAG <= 4 ? 4 : 8;
static_assert(LAG <= 6, "depth of the rings");
constexpr int MAIL_UNIT = 65536, NUNIT = 88;
__device__ __align__(1024) uint8_t g_xn[2][32 * 10 * 8192];
__device__ __align__(1024) uint8_t g_xnb[8][81920];
__device__ __align__(1024) uint8_t g_ob[8][2][40960];
__device__ __align__(1024) uint8_t g_o[8][2][96][4096];
__device__ __align__(1024) uint8_t g_part[MD][2][16 * 2560];
__device__ __align__(1024) uint8_t g_prod[MD][2][16 * 2560];
__device__ __align__(8192) uint8_t g_mbuf[3][40960];
__device__ __align__(8192) uint8_t g_mail[NUNIT + 1][MAIL_UNIT];
__device__ uint32_t g_sel[NUNIT];
__device__ __align__(1024) uint8_t g_rot[96][32768];
__device__ __align__(128) uint8_t g_xs[3][SEQ * DM * 2];
enum { CN_O = 0, CN_L = 1, CN_A = 2, CN_X = 3, CN_Z = 4, CN_P = 5 };
__device__ __align__(128) uint32_t g_cnt[6][NS + 1][6 * 32];
__device__ int g_err;
#define DUR(i)
#define TS(jj, i)
#define PTS(i)
#define TSB(jj, i)
#define TSV(jj, i, v)
#define TS_FLUSH(jj)
#define WTS(i, k)
#define WW -1

__device__ __forceinline__ uint32_t smem_u32(const void* p) { return (uint32_t)__cvta_generic_to_shared(p); }
__device__ __forceinline__ uint32_t clk32() { unsigned long long t; asm volatile("mov.u64 %0, %%clock64;" : "=l"(t)::"memory"); return (uint32_t)t; }
__device__ __forceinline__ uint32_t mapa(uint32_t a, uint32_t r) { uint32_t o; asm("mapa.shared::cluster.u32 %0,%1,%2;" : "=r"(o) : "r"(a), "r"(r)); return o; }
__device__ __forceinline__ void mbar_init(uint32_t bar, uint32_t cnt) { asm volatile("mbarrier.init.shared::cta.b64 [%0],%1;" ::"r"(bar), "r"(cnt) : "memory"); }
__device__ __forceinline__ void mbar_expect_tx(uint32_t bar, uint32_t bytes) { asm volatile("mbarrier.arrive.expect_tx.shared::cta.b64 _,[%0],%1;" ::"r"(bar), "r"(bytes) : "memory"); }
__device__ __forceinline__ void mbar_arrive(uint32_t bar) { asm volatile("mbarrier.arrive.shared::cta.b64 _,[%0];" ::"r"(bar) : "memory"); }
__device__ __forceinline__ void mbar_arrive_cluster(uint32_t bar) { asm volatile("mbarrier.arrive.shared::cluster.b64 _,[%0];" ::"r"(bar) : "memory"); }
__device__ __forceinline__ bool mbar_try(uint32_t bar, uint32_t ph) {
  uint32_t ok;
  asm volatile("{.reg .pred p; mbarrier.try_wait.parity.shared::cta.b64 p,[%1],%2; selp.u32 %0,1,0,p;}" : "=r"(ok) : "r"(bar), "r"(ph) : "memory");
  return ok;
}
__device__ __forceinline__ bool mbar_test(uint32_t bar, uint32_t ph) {
  uint32_t ok;
  asm volatile("{.reg .pred p; mbarrier.test_wait.parity.shared::cta.b64 p,[%1],%2; selp.u32 %0,1,0,p;}" : "=r"(ok) : "r"(bar), "r"(ph) : "memory");
  return ok;
}
__device__ __forceinline__ void mbar_wait(uint32_t bar, uint32_t ph, int& left) {
  asm volatile("{\n.reg .pred p;\nW: mbarrier.try_wait.parity.shared::cta.b64 p,[%1],%2;\nadd.s32 %0,%0,-1;\nsetp.gt.and.s32 p,%0,0,!p;\n@p bra.uni W;\n}"
               : "+r"(left) : "r"(bar), "r"(ph) : "memory");
}
__device__ __forceinline__ bool elect() {
  uint32_t p;
  asm volatile("{.reg .pred p; elect.sync _|p,0xffffffff; selp.u32 %0,1,0,p;}" : "=r"(p));
  return p;
}
__device__ __forceinline__ int fresh(int x) { asm volatile("" : "+r"(x)); return x; }
__device__ __forceinline__ void bar_sync(int id, int n) { asm volatile("bar.sync %0,%1;" ::"r"(id), "r"(n) : "memory"); }
__device__ __forceinline__ void bar_arrive(int id, int n) { asm volatile("bar.arrive %0,%1;" ::"r"(id), "r"(n) : "memory"); }
__device__ __forceinline__ bool bar_red_or(int id, int n, bool v) {
  uint32_t r;
  asm volatile("{\n .reg .pred p, q;\n setp.ne.u32 q, %3, 0;\n barrier.cta.red.or.pred p, %1, %2, q;\n selp.u32 %0, 1, 0, p;\n}" : "=r"(r) : "r"(id), "r"(n), "r"((uint32_t)v) : "memory");
  return r != 0;
}
__device__ __forceinline__ void cluster_sync() {
  asm volatile("barrier.cluster.arrive.release.aligned;" ::: "memory");
  asm volatile("barrier.cluster.wait.acquire.aligned;" ::: "memory");
}
__device__ __forceinline__ void fence_async() { asm volatile("fence.proxy.async.shared::cta;" ::: "memory"); }
__device__ __forceinline__ void bulk_g2s(uint32_t dst, const void* src, uint32_t bytes, uint32_t bar) {
  asm volatile("cp.async.bulk.shared::cluster.global.mbarrier::complete_tx::bytes [%0],[%1],%2,[%3];" ::"r"(dst), "l"(src), "r"(bytes), "r"(bar) : "memory");
}
__device__ __forceinline__ void bulk_g2s_mc(uint32_t dst, const void* src, uint32_t bytes, uint32_t bar) {
  asm volatile("cp.async.bulk.shared::cluster.global.mbarrier::complete_tx::bytes.multicast::cluster [%0],[%1],%2,[%3],%4;"
               ::"r"(dst), "l"(src), "r"(bytes), "r"(bar), "h"((uint16_t)7) : "memory");
}
__device__ __forceinline__ void bulk_s2g(void* dst, uint32_t src, uint32_t bytes) {
  asm volatile("cp.async.bulk.global.shared::cta.bulk_group [%0],[%1],%2;" ::"l"(dst), "r"(src), "r"(bytes) : "memory");
}
__device__ __forceinline__ void bulk_s2c(uint32_t dst, uint32_t src, uint32_t bytes, uint32_t bar) {
  asm volatile("cp.async.bulk.shared::cluster.shared::cta.mbarrier::complete_tx::bytes [%0],[%1],%2,[%3];" ::"r"(dst), "r"(src), "r"(bytes), "r"(bar) : "memory");
}
__device__ __forceinline__ void bulk_commit() { asm volatile("cp.async.bulk.commit_group;" ::: "memory"); }
__device__ __forceinline__ void bulk_wait_read() { asm volatile("cp.async.bulk.wait_group.read 0;" ::: "memory"); }
__device__ __forceinline__ void bulk_wait() { asm volatile("cp.async.bulk.wait_group 0;" ::: "memory"); }
__device__ __forceinline__ void tma2d(uint32_t dst, const CUtensorMap* tm, int c0, int c1, uint32_t bar) {
  asm volatile("cp.async.bulk.tensor.2d.shared::cluster.global.mbarrier::complete_tx::bytes [%0],[%1,{%3,%4}],[%2];"
               ::"r"(dst), "l"(tm), "r"(bar), "r"(c0), "r"(c1) : "memory");
}
__device__ __forceinline__ void tma3d_mc(uint32_t dst, const CUtensorMap* tm, int c0, int c1, int c2, uint32_t bar) {
  asm volatile("cp.async.bulk.tensor.3d.shared::cluster.global.mbarrier::complete_tx::bytes.multicast::cluster [%0],[%1,{%3,%4,%5}],[%2],%6;"
               ::"r"(dst), "l"(tm), "r"(bar), "r"(c0), "r"(c1), "r"(c2), "h"((uint16_t)7) : "memory");
}
__device__ __forceinline__ uint32_t pack_bf16(float lo, float hi) {
  uint32_t r; asm("cvt.rn.bf16x2.f32 %0,%1,%2;" : "=r"(r) : "f"(hi), "f"(lo)); return r;
}
__device__ __forceinline__ uint32_t pack_h2(float lo, float hi) {
  uint32_t r; asm("cvt.rn.satfinite.f16x2.f32 %0,%1,%2;" : "=r"(r) : "f"(hi), "f"(lo)); return r;
}
__device__ __forceinline__ float2 unpack_h2(uint32_t x) {
  float2 r; asm("{.reg .b16 l,h; mov.b32 {l,h},%2; cvt.f32.f16 %0,l; cvt.f32.f16 %1,h;}" : "=f"(r.x), "=f"(r.y) : "r"(x)); return r;
}
__device__ __forceinline__ uint32_t add_h2(uint32_t a, uint32_t b) { uint32_t r; asm("add.rn.f16x2 %0,%1,%2;" : "=r"(r) : "r"(a), "r"(b)); return r; }
__device__ __forceinline__ uint32_t max_h2(uint32_t a, uint32_t b) { uint32_t r; asm("max.f16x2 %0,%1,%2;" : "=r"(r) : "r"(a), "r"(b)); return r; }
__device__ __forceinline__ float bf_lo(uint32_t x) { return __uint_as_float(x << 16); }
__device__ __forceinline__ float bf_hi(uint32_t x) { return __uint_as_float(x & 0xFFFF0000u); }
__device__ __forceinline__ float ex2(float x) { float y; asm("ex2.approx.ftz.f32 %0,%1;" : "=f"(y) : "f"(x)); return y; }
__device__ __forceinline__ void ldsm4t(uint32_t (&r)[4], uint32_t a) {
  asm volatile("ldmatrix.sync.aligned.m8n8.x4.trans.shared.b16 {%0,%1,%2,%3},[%4];" : "=r"(r[0]), "=r"(r[1]), "=r"(r[2]), "=r"(r[3]) : "r"(a) : "memory");
}
__device__ __forceinline__ void stsm4(uint32_t a, uint32_t r0, uint32_t r1, uint32_t r2, uint32_t r3) {
  asm volatile("stmatrix.sync.aligned.m8n8.x4.shared.b16 [%0],{%1,%2,%3,%4};" ::"r"(a), "r"(r0), "r"(r1), "r"(r2), "r"(r3) : "memory");
}
__device__ __forceinline__ void stsm4t(uint32_t a, uint32_t r0, uint32_t r1, uint32_t r2, uint32_t r3) {
  asm volatile("stmatrix.sync.aligned.m8n8.x4.trans.shared.b16 [%0],{%1,%2,%3,%4};" ::"r"(a), "r"(r0), "r"(r1), "r"(r2), "r"(r3) : "memory");
}
__device__ __forceinline__ void stsm2(uint32_t a, uint32_t r0, uint32_t r1) {
  asm volatile("stmatrix.sync.aligned.m8n8.x2.shared.b16 [%0],{%1,%2};" ::"r"(a), "r"(r0), "r"(r1) : "memory");
}
__device__ __forceinline__ void sts32(uint32_t a, uint32_t v) { asm volatile("st.shared.b32 [%0],%1;" ::"r"(a), "r"(v) : "memory"); }
__device__ __forceinline__ void sts128(uint32_t a, uint4 v) { asm volatile("st.shared.v4.b32 [%0],{%1,%2,%3,%4};" ::"r"(a), "r"(v.x), "r"(v.y), "r"(v.z), "r"(v.w) : "memory"); }
__device__ __forceinline__ uint32_t lds32(uint32_t a) { uint32_t v; asm volatile("ld.shared.b32 %0,[%1];" : "=r"(v) : "r"(a) : "memory"); return v; }
__device__ __forceinline__ uint2 lds64(uint32_t a) { uint2 v; asm volatile("ld.shared.v2.b32 {%0,%1},[%2];" : "=r"(v.x), "=r"(v.y) : "r"(a) : "memory"); return v; }
__device__ __forceinline__ uint4 lds128(uint32_t a) { uint4 v; asm volatile("ld.shared.v4.b32 {%0,%1,%2,%3},[%4];" : "=r"(v.x), "=r"(v.y), "=r"(v.z), "=r"(v.w) : "r"(a) : "memory"); return v; }
__device__ __forceinline__ void st_async1(uint32_t a, uint32_t x, uint32_t bar) {
  asm volatile("st.async.weak.shared::cluster.mbarrier::complete_tx::bytes.b32 [%0],%1,[%2];" ::"r"(a), "r"(x), "r"(bar) : "memory");
}
__device__ __forceinline__ void st_async2(uint32_t a, uint32_t x, uint32_t y, uint32_t bar) {
  asm volatile("st.async.weak.shared::cluster.mbarrier::complete_tx::bytes.v2.b32 [%0],{%1,%2},[%3];" ::"r"(a), "r"(x), "r"(y), "r"(bar) : "memory");
}
__device__ __forceinline__ void st_async4(uint32_t a, uint32_t x, uint32_t y, uint32_t z, uint32_t w, uint32_t bar) {
  asm volatile("st.async.weak.shared::cluster.mbarrier::complete_tx::bytes.v4.b32 [%0],{%1,%2,%3,%4},[%5];" ::"r"(a), "r"(x), "r"(y), "r"(z), "r"(w), "r"(bar) : "memory");
}
__device__ __forceinline__ uint32_t ld_relaxed(const void* p) {
  uint32_t v; asm volatile("ld.relaxed.gpu.global.u32 %0,[%1];" : "=r"(v) : "l"(p) : "memory"); return v;
}
__device__ __forceinline__ void st_relaxed(void* p, uint32_t v) { asm volatile("st.relaxed.gpu.global.b32 [%0],%1;" ::"l"(p), "r"(v) : "memory"); }
__device__ __forceinline__ void ld_msg16x4(uint4* x, const void* p) {
  asm volatile("{.reg .b128 a,b,c,d;\n ld.relaxed.gpu.global.b128 a,[%16]; ld.relaxed.gpu.global.b128 b,[%16+512];\n"
               "ld.relaxed.gpu.global.b128 c,[%16+1024]; ld.relaxed.gpu.global.b128 d,[%16+1536];\n"
               "mov.b128 {%0,%1,%2,%3},a; mov.b128 {%4,%5,%6,%7},b; mov.b128 {%8,%9,%10,%11},c; mov.b128 {%12,%13,%14,%15},d;}"
               : "=r"(x[0].x), "=r"(x[0].y), "=r"(x[0].z), "=r"(x[0].w), "=r"(x[1].x), "=r"(x[1].y), "=r"(x[1].z), "=r"(x[1].w),
                 "=r"(x[2].x), "=r"(x[2].y), "=r"(x[2].z), "=r"(x[2].w), "=r"(x[3].x), "=r"(x[3].y), "=r"(x[3].z), "=r"(x[3].w)
               : "l"(p) : "memory");
}
__device__ __forceinline__ uint32_t differ4(uint32_t a, uint32_t b, uint32_t c, uint32_t d, uint32_t t) {
  uint32_t r;
  asm volatile("{.reg .b32 u,v; lop3.b32 u,%1,%2,%5,0x7e; lop3.b32 v,%3,%4,%5,0x7e; or.b32 %0,u,v;}" : "=r"(r) : "r"(a), "r"(b), "r"(c), "r"(d), "r"(t));
  return r;
}
__device__ __forceinline__ void st_msg16(void* p, uint32_t x, uint32_t y, uint32_t z, uint32_t w) {
  asm volatile("{.reg .b128 r; mov.b128 r,{%1,%2,%3,%4}; st.relaxed.gpu.global.b128 [%0],r;}" ::"l"(p), "r"(x), "r"(y), "r"(z), "r"(w) : "memory");
}
__device__ __forceinline__ void ld_msg16x2(uint4* x, const void* p) {
  asm volatile("{.reg .b128 a,b;\n ld.relaxed.gpu.global.b128 a,[%8]; ld.relaxed.gpu.global.b128 b,[%8+512];\n"
               "mov.b128 {%0,%1,%2,%3},a; mov.b128 {%4,%5,%6,%7},b;}"
               : "=r"(x[0].x), "=r"(x[0].y), "=r"(x[0].z), "=r"(x[0].w), "=r"(x[1].x), "=r"(x[1].y), "=r"(x[1].z), "=r"(x[1].w)
               : "l"(p) : "memory");
}
__device__ __forceinline__ void ld_msg16x6(uint4* x, const void* p, const void* q) {
  asm volatile("{.reg .b128 a,b,c,d,e,f;\n ld.relaxed.gpu.global.b128 a,[%24]; ld.relaxed.gpu.global.b128 b,[%24+512];\n"
               "ld.relaxed.gpu.global.b128 c,[%24+1024]; ld.relaxed.gpu.global.b128 d,[%24+1536];\n"
               "ld.relaxed.gpu.global.b128 e,[%25]; ld.relaxed.gpu.global.b128 f,[%25+512];\n"
               "mov.b128 {%0,%1,%2,%3},a; mov.b128 {%4,%5,%6,%7},b; mov.b128 {%8,%9,%10,%11},c; mov.b128 {%12,%13,%14,%15},d;\n"
               "mov.b128 {%16,%17,%18,%19},e; mov.b128 {%20,%21,%22,%23},f;}"
               : "=r"(x[0].x), "=r"(x[0].y), "=r"(x[0].z), "=r"(x[0].w), "=r"(x[1].x), "=r"(x[1].y), "=r"(x[1].z), "=r"(x[1].w),
                 "=r"(x[2].x), "=r"(x[2].y), "=r"(x[2].z), "=r"(x[2].w), "=r"(x[3].x), "=r"(x[3].y), "=r"(x[3].z), "=r"(x[3].w),
                 "=r"(x[4].x), "=r"(x[4].y), "=r"(x[4].z), "=r"(x[4].w), "=r"(x[5].x), "=r"(x[5].y), "=r"(x[5].z), "=r"(x[5].w)
               : "l"(p), "l"(q) : "memory");
}
__device__ __forceinline__ uint32_t ld_acquire(const void* p) {
  uint32_t v; asm volatile("ld.acquire.gpu.global.u32 %0,[%1];" : "=r"(v) : "l"(p) : "memory"); return v;
}
__device__ __forceinline__ float4 ld_relaxed4f(const void* p) {
  float4 v; asm volatile("ld.relaxed.gpu.global.v4.f32 {%0,%1,%2,%3},[%4];" : "=f"(v.x), "=f"(v.y), "=f"(v.z), "=f"(v.w) : "l"(p) : "memory"); return v;
}
__device__ __forceinline__ float2 ld_relaxed2f(const void* p) {
  float2 v; asm volatile("ld.relaxed.gpu.global.v2.f32 {%0,%1},[%2];" : "=f"(v.x), "=f"(v.y) : "l"(p) : "memory"); return v;
}
__device__ __forceinline__ void prefetch_l2(const void* p) { asm volatile("prefetch.global.L2 [%0];" ::"l"(p)); }
__device__ __forceinline__ void fence_async_all() { asm volatile("fence.proxy.async.global;" ::: "memory"); }
__device__ __forceinline__ void cnt_signal(uint32_t* p) { asm volatile("red.release.gpu.global.add.u32 [%0],1;" ::"l"(p) : "memory"); }

__host__ __device__ __forceinline__ constexpr uint64_t mkdesc(uint32_t addr, uint32_t lbo, uint32_t sbo) {
  return (uint64_t)((addr & 0x3FFFF) >> 4) | ((uint64_t)(lbo >> 4) << 16) | ((uint64_t)(sbo >> 4) << 32) | ((uint64_t)1 << 62);
}
__host__ __device__ __forceinline__ constexpr uint64_t mkdesc64(uint32_t addr, uint32_t lbo, uint32_t sbo) {
  return (uint64_t)((addr & 0x3FFFF) >> 4) | ((uint64_t)(lbo >> 4) << 16) | ((uint64_t)(sbo >> 4) << 32) | ((uint64_t)2 << 62);
}
__host__ __device__ __forceinline__ constexpr uint64_t mkdesc_ns(uint32_t addr, uint32_t lbo, uint32_t sbo) {
  return (uint64_t)((addr & 0x3FFFF) >> 4) | ((uint64_t)(lbo >> 4) << 16) | ((uint64_t)(sbo >> 4) << 32);
}
__device__ __forceinline__ void wg_fence() { asm volatile("wgmma.fence.sync.aligned;" ::: "memory"); }
__device__ __forceinline__ void wg_commit() { asm volatile("wgmma.commit_group.sync.aligned;" ::: "memory"); }
template <int N> __device__ __forceinline__ void wg_wait() { asm volatile("wgmma.wait_group.sync.aligned %0;" ::"n"(N) : "memory"); }

__device__ __forceinline__ void wgmma_rs32(float (&d)[16], const uint32_t (&a)[4], uint64_t db, int sc) {
  asm volatile("{.reg .pred p; setp.ne.b32 p,%21,0; wgmma.mma_async.sync.aligned.m64n32k16.f32.bf16.bf16 "
               "{%0,%1,%2,%3,%4,%5,%6,%7,%8,%9,%10,%11,%12,%13,%14,%15},{%16,%17,%18,%19},%20,p,1,1,0;}"
               : "+f"(d[0]), "+f"(d[1]), "+f"(d[2]), "+f"(d[3]), "+f"(d[4]), "+f"(d[5]), "+f"(d[6]), "+f"(d[7]),
                 "+f"(d[8]), "+f"(d[9]), "+f"(d[10]), "+f"(d[11]), "+f"(d[12]), "+f"(d[13]), "+f"(d[14]), "+f"(d[15])
               : "r"(a[0]), "r"(a[1]), "r"(a[2]), "r"(a[3]), "l"(db), "r"(sc));
}
__device__ __forceinline__ void wgmma_rt32(float (&d)[16], const uint32_t (&a)[4], uint64_t db, int sc) {
  asm volatile("{.reg .pred p; setp.ne.b32 p,%21,0; wgmma.mma_async.sync.aligned.m64n32k16.f32.bf16.bf16 "
               "{%0,%1,%2,%3,%4,%5,%6,%7,%8,%9,%10,%11,%12,%13,%14,%15},{%16,%17,%18,%19},%20,p,1,1,1;}"
               : "+f"(d[0]), "+f"(d[1]), "+f"(d[2]), "+f"(d[3]), "+f"(d[4]), "+f"(d[5]), "+f"(d[6]), "+f"(d[7]),
                 "+f"(d[8]), "+f"(d[9]), "+f"(d[10]), "+f"(d[11]), "+f"(d[12]), "+f"(d[13]), "+f"(d[14]), "+f"(d[15])
               : "r"(a[0]), "r"(a[1]), "r"(a[2]), "r"(a[3]), "l"(db), "r"(sc));
}
__device__ __forceinline__ void wgmma_rs48(float (&d)[24], const uint32_t (&a)[4], uint64_t db, int sc) {
  asm volatile("{.reg .pred p; setp.ne.b32 p,%29,0; wgmma.mma_async.sync.aligned.m64n48k16.f32.bf16.bf16 "
               "{%0,%1,%2,%3,%4,%5,%6,%7,%8,%9,%10,%11,%12,%13,%14,%15,%16,%17,%18,%19,%20,%21,%22,%23},{%24,%25,%26,%27},%28,p,1,1,0;}"
               : "+f"(d[0]), "+f"(d[1]), "+f"(d[2]), "+f"(d[3]), "+f"(d[4]), "+f"(d[5]), "+f"(d[6]), "+f"(d[7]),
                 "+f"(d[8]), "+f"(d[9]), "+f"(d[10]), "+f"(d[11]), "+f"(d[12]), "+f"(d[13]), "+f"(d[14]), "+f"(d[15]),
                 "+f"(d[16]), "+f"(d[17]), "+f"(d[18]), "+f"(d[19]), "+f"(d[20]), "+f"(d[21]), "+f"(d[22]), "+f"(d[23])
               : "r"(a[0]), "r"(a[1]), "r"(a[2]), "r"(a[3]), "l"(db), "r"(sc));
}
__device__ __forceinline__ void wgmma_ts32(float (&d)[16], uint64_t da, uint64_t db, int sc) {
  asm volatile("{.reg .pred p; setp.ne.b32 p,%18,0; wgmma.mma_async.sync.aligned.m64n32k16.f32.bf16.bf16 "
               "{%0,%1,%2,%3,%4,%5,%6,%7,%8,%9,%10,%11,%12,%13,%14,%15},%16,%17,p,1,1,1,0;}"
               : "+f"(d[0]), "+f"(d[1]), "+f"(d[2]), "+f"(d[3]), "+f"(d[4]), "+f"(d[5]), "+f"(d[6]), "+f"(d[7]),
                 "+f"(d[8]), "+f"(d[9]), "+f"(d[10]), "+f"(d[11]), "+f"(d[12]), "+f"(d[13]), "+f"(d[14]), "+f"(d[15])
               : "l"(da), "l"(db), "r"(sc));
}
__device__ __forceinline__ void wgmma_tt32(float (&d)[16], uint64_t da, uint64_t db, int sc) {
  asm volatile("{.reg .pred p; setp.ne.b32 p,%18,0; wgmma.mma_async.sync.aligned.m64n32k16.f32.bf16.bf16 "
               "{%0,%1,%2,%3,%4,%5,%6,%7,%8,%9,%10,%11,%12,%13,%14,%15},%16,%17,p,1,1,1,1;}"
               : "+f"(d[0]), "+f"(d[1]), "+f"(d[2]), "+f"(d[3]), "+f"(d[4]), "+f"(d[5]), "+f"(d[6]), "+f"(d[7]),
                 "+f"(d[8]), "+f"(d[9]), "+f"(d[10]), "+f"(d[11]), "+f"(d[12]), "+f"(d[13]), "+f"(d[14]), "+f"(d[15])
               : "l"(da), "l"(db), "r"(sc));
}
__device__ __forceinline__ void wgmma_ts48(float (&d)[24], uint64_t da, uint64_t db, int sc) {
  asm volatile("{.reg .pred p; setp.ne.b32 p,%26,0; wgmma.mma_async.sync.aligned.m64n48k16.f32.bf16.bf16 "
               "{%0,%1,%2,%3,%4,%5,%6,%7,%8,%9,%10,%11,%12,%13,%14,%15,%16,%17,%18,%19,%20,%21,%22,%23},%24,%25,p,1,1,1,0;}"
               : "+f"(d[0]), "+f"(d[1]), "+f"(d[2]), "+f"(d[3]), "+f"(d[4]), "+f"(d[5]), "+f"(d[6]), "+f"(d[7]),
                 "+f"(d[8]), "+f"(d[9]), "+f"(d[10]), "+f"(d[11]), "+f"(d[12]), "+f"(d[13]), "+f"(d[14]), "+f"(d[15]),
                 "+f"(d[16]), "+f"(d[17]), "+f"(d[18]), "+f"(d[19]), "+f"(d[20]), "+f"(d[21]), "+f"(d[22]), "+f"(d[23])
               : "l"(da), "l"(db), "r"(sc));
}
__device__ __forceinline__ void wgmma_ts64(float (&d)[32], uint64_t da, uint64_t db, int sc) {
  asm volatile("{.reg .pred p; setp.ne.b32 p,%34,0; wgmma.mma_async.sync.aligned.m64n64k16.f32.bf16.bf16 "
               "{%0,%1,%2,%3,%4,%5,%6,%7,%8,%9,%10,%11,%12,%13,%14,%15,%16,%17,%18,%19,%20,%21,%22,%23,%24,%25,%26,%27,%28,%29,%30,%31},%32,%33,p,1,1,1,0;}"
               : "+f"(d[0]), "+f"(d[1]), "+f"(d[2]), "+f"(d[3]), "+f"(d[4]), "+f"(d[5]), "+f"(d[6]), "+f"(d[7]),
                 "+f"(d[8]), "+f"(d[9]), "+f"(d[10]), "+f"(d[11]), "+f"(d[12]), "+f"(d[13]), "+f"(d[14]), "+f"(d[15]),
                 "+f"(d[16]), "+f"(d[17]), "+f"(d[18]), "+f"(d[19]), "+f"(d[20]), "+f"(d[21]), "+f"(d[22]), "+f"(d[23]),
                 "+f"(d[24]), "+f"(d[25]), "+f"(d[26]), "+f"(d[27]), "+f"(d[28]), "+f"(d[29]), "+f"(d[30]), "+f"(d[31])
               : "l"(da), "l"(db), "r"(sc));
}
__device__ __forceinline__ void wgmma_tt40(float (&d)[20], uint64_t da, uint64_t db, int sc) {
  asm volatile("{.reg .pred p; setp.ne.b32 p,%22,0; wgmma.mma_async.sync.aligned.m64n40k16.f32.bf16.bf16 "
               "{%0,%1,%2,%3,%4,%5,%6,%7,%8,%9,%10,%11,%12,%13,%14,%15,%16,%17,%18,%19},%20,%21,p,1,1,1,1;}"
               : "+f"(d[0]), "+f"(d[1]), "+f"(d[2]), "+f"(d[3]), "+f"(d[4]), "+f"(d[5]), "+f"(d[6]), "+f"(d[7]),
                 "+f"(d[8]), "+f"(d[9]), "+f"(d[10]), "+f"(d[11]), "+f"(d[12]), "+f"(d[13]), "+f"(d[14]), "+f"(d[15]),
                 "+f"(d[16]), "+f"(d[17]), "+f"(d[18]), "+f"(d[19])
               : "l"(da), "l"(db), "r"(sc));
}
__device__ __forceinline__ void wgmma_ss8(float (&d)[4], uint64_t da, uint64_t db, int sc) {
  asm volatile("{.reg .pred p; setp.ne.b32 p,%6,0; wgmma.mma_async.sync.aligned.m64n8k16.f32.bf16.bf16 "
               "{%0,%1,%2,%3},%4,%5,p,1,1,0,0;}"
               : "+f"(d[0]), "+f"(d[1]), "+f"(d[2]), "+f"(d[3])
               : "l"(da), "l"(db), "r"(sc));
}
__device__ __forceinline__ void wgmma_ss32(float (&d)[16], uint64_t da, uint64_t db, int sc) {
  asm volatile("{.reg .pred p; setp.ne.b32 p,%18,0; wgmma.mma_async.sync.aligned.m64n32k16.f32.bf16.bf16 "
               "{%0,%1,%2,%3,%4,%5,%6,%7,%8,%9,%10,%11,%12,%13,%14,%15},%16,%17,p,1,1,0,0;}"
               : "+f"(d[0]), "+f"(d[1]), "+f"(d[2]), "+f"(d[3]), "+f"(d[4]), "+f"(d[5]), "+f"(d[6]), "+f"(d[7]),
                 "+f"(d[8]), "+f"(d[9]), "+f"(d[10]), "+f"(d[11]), "+f"(d[12]), "+f"(d[13]), "+f"(d[14]), "+f"(d[15])
               : "l"(da), "l"(db), "r"(sc));
}
__device__ __forceinline__ void wgmma_tt16(float (&d)[8], uint64_t da, uint64_t db, int sc) {
  asm volatile("{.reg .pred p; setp.ne.b32 p,%10,0; wgmma.mma_async.sync.aligned.m64n16k16.f32.bf16.bf16 "
               "{%0,%1,%2,%3,%4,%5,%6,%7},%8,%9,p,1,1,1,1;}"
               : "+f"(d[0]), "+f"(d[1]), "+f"(d[2]), "+f"(d[3]), "+f"(d[4]), "+f"(d[5]), "+f"(d[6]), "+f"(d[7])
               : "l"(da), "l"(db), "r"(sc));
}

__device__ __forceinline__ void ln_row_to_image(const bf16* __restrict__ x, uint4* st, int row, int lane) {
  const uint4* src = reinterpret_cast<const uint4*>(x + (size_t)row * DM);
  uint4 v[3];
  v[0] = src[lane]; v[1] = src[lane + 32];
  v[2] = lane < 16 ? src[lane + 64] : make_uint4(0, 0, 0, 0);
  float s = 0.f;
#pragma unroll
  for (int i = 0; i < 3; i++) {
    s += bf_lo(v[i].x) + bf_hi(v[i].x) + bf_lo(v[i].y) + bf_hi(v[i].y) + bf_lo(v[i].z) + bf_hi(v[i].z) + bf_lo(v[i].w) + bf_hi(v[i].w);
  }
#pragma unroll
  for (int o = 16; o > 0; o >>= 1) s += __shfl_xor_sync(0xffffffffu, s, o);
  const float mean = s * (1.f / DM);
  float q = 0.f;
#pragma unroll
  for (int i = 0; i < 3; i++) {
    if (i < 2 || lane < 16) {
      const uint32_t w[4] = {v[i].x, v[i].y, v[i].z, v[i].w};
#pragma unroll
      for (int j = 0; j < 4; j++) { float a = bf_lo(w[j]) - mean, b = bf_hi(w[j]) - mean; q += a * a + b * b; }
    }
  }
#pragma unroll
  for (int o = 16; o > 0; o >>= 1) q += __shfl_xor_sync(0xffffffffu, q, o);
  const float rstd = rsqrtf(q * (1.f / DM) + 1e-5f);
#pragma unroll
  for (int i = 0; i < 3; i++) {
    if (i < 2 || lane < 16) {
      const int c = lane + 32 * i;
      uint4 o;
      o.x = pack_bf16((bf_lo(v[i].x) - mean) * rstd, (bf_hi(v[i].x) - mean) * rstd);
      o.y = pack_bf16((bf_lo(v[i].y) - mean) * rstd, (bf_hi(v[i].y) - mean) * rstd);
      o.z = pack_bf16((bf_lo(v[i].z) - mean) * rstd, (bf_hi(v[i].z) - mean) * rstd);
      o.w = pack_bf16((bf_lo(v[i].w) - mean) * rstd, (bf_hi(v[i].w) - mean) * rstd);
      st[c * 8 + ((row ^ c) & 7)] = o;
    }
  }
}

__global__ void __launch_bounds__(256) k_pre(const bf16* __restrict__ x, const bf16* __restrict__ mem0) {
  const int row = blockIdx.x * 8 + (threadIdx.x >> 5);
  __shared__ uint4 st[640];
  ln_row_to_image(x, st, row, threadIdx.x & 31);
  __syncthreads();
  for (int i = threadIdx.x; i < 640; i += 256) reinterpret_cast<uint4*>(g_xn[0])[blockIdx.x * 640 + i] = st[(i & ~7) | ((i ^ (i >> 3)) & 7)];
  const int gt = blockIdx.x * 256 + threadIdx.x;
  const uint4 sent = make_uint4(SENT, SENT, SENT, SENT);
  if (gt < NUNIT) g_sel[gt] = 0;
  if (gt < 3 * 2560) {
    const int i = gt % 2560, p = ((i >> 9) * 256 + (i & 255)) % 640;
    reinterpret_cast<uint4*>(&g_mbuf[0][0])[gt] = gt < 5120 ? sent : *reinterpret_cast<const uint4*>(mem0 + (p & 7) * DM + (p >> 3) * 8);
  }
  if (gt < 6 * (NS + 1) * 6) (&g_cnt[0][0][0])[gt * 32] = 0;
}

namespace C {
constexpr int OFF_WK = 0;
constexpr int OFF_WO = 81920;
constexpr int OFF_WXQ = 131072;
constexpr int OFF_WXV = 133120;
constexpr int STAGE_Q = 51200, STAGE_V = 133120;
constexpr int OFF_R = 139264;
constexpr int OFF_OG = OFF_R + 16384;
constexpr int OFF_RING = 180224;
constexpr int OFF_SCR = OFF_RING + 49152;
constexpr int SLOT = 6144;
__host__ __device__ constexpr int slot_off(int c) { return c < 3 ? OFF_R + 22528 + c * SLOT : c < 6 ? OFF_RING + (c - 3) * SLOT : OFF_RING + 20480 + (c - 6) * SLOT; }
constexpr int OFF_QT = OFF_RING;
constexpr int OFF_KT = OFF_RING + 10240;
constexpr int OFF_VT = OFF_RING + 20480;
constexpr int OFF_P = OFF_RING + 30720;
constexpr int OFF_XL = OFF_P + 7680;
constexpr int OFF_XM = OFF_XL + 10752;
__host__ __device__ constexpr int xl_off(int w) { return OFF_XL + (w ? w * 1152 - 512 : 0); }
constexpr int OFF_BAR = 231424;
constexpr int OFF_TS = OFF_BAR + 256;
constexpr int SMEM = 232448;
constexpr uint32_t SB0 = 1024;
constexpr int BAR_F0 = OFF_BAR, BAR_F1 = OFF_BAR + 8, BAR_F2 = OFF_BAR + 16,
              BAR_W1 = OFF_BAR + 80, BAR_W2 = OFF_BAR + 88, BAR_W3 = OFF_BAR + 96, BAR_X = OFF_BAR + 32,
              BAR_OG2 = OFF_BAR + 104, BAR_XE = OFF_BAR + 112,
              BAR_OG = OFF_BAR + 120, BAR_OE = OFF_BAR + 128, BAR_ROT = OFF_BAR + 136, BAR_RQ = OFF_BAR + 168, BAR_VF = OFF_BAR + 144, BAR_RF = OFF_BAR + 152,
              BAR_RE = OFF_BAR + 160, BAR_RID = OFF_BAR + 24, BAR_M = OFF_BAR + 176,
              OFF_SEL = OFF_BAR + 224;
constexpr int NB_M = 1, NB_QK = 2, NB_P = 3, NB_V = 4, NB_MR = 5, NB_GO = 6, NB_O = 7, NB_BQ = 8, NB_BV = 9, NB_S = 10, NB_X = 11, NB_M2 = 15;
#define B1 300
#define B2 400
#define B3 1500
#define OSP 0
#define PL2 1
#define PL1 1
#define OGF 1
#define PFD 3
constexpr float SCL = 0.07216878364870322f * 1.4426950408889634f;
__host__ __device__ constexpr int wo_off(int u) { return u < 2 ? OFF_RING + u * 8192 : u < 8 ? OFF_WO + (u - 2) * 8192 : OFF_R + (u - 8) * 8192; }
}

struct ChainArgs {
  const uint8_t* xn;
  uint8_t* oimg;
  uint8_t* mbuf;
  uint8_t* mail;
  uint8_t* rot;
  int ten;
  uint64_t td[40], rd[40], kd[44], od[40], gd[12], sd[16], vd[5], pd[12];
};

template <int NK>
__device__ __forceinline__ void load_wfrags(uint32_t (&a)[NK][4], uint32_t base, int w, int lane) {
  const int i = lane >> 3, r = lane & 7;
  const int chunk = 2 * w + (i & 1);
  const uint32_t a0 = base + (r + (i >> 1) * 8) * 128 + ((chunk ^ r) << 4);
#pragma unroll
  for (int k = 0; k < NK; k++) ldsm4t(a[k], a0 + k * 2048);
}
__device__ __forceinline__ uint64_t desc2(uint32_t lo, uint32_t hi) { uint64_t d; asm("mov.b64 %0,{%1,%2};" : "=l"(d) : "r"(lo), "r"(hi)); return d; }
__host__ __device__ __forceinline__ constexpr uint64_t wdesc(int off) { return mkdesc(C::SB0 + off, 8192, 1024); }
__host__ __device__ __forceinline__ constexpr uint64_t rdesc(int k) { return mkdesc_ns(C::SB0 + C::OFF_R + k * 256, 128, 10240); }
__host__ __device__ __forceinline__ constexpr uint64_t tdesc(int k) { return mkdesc_ns(C::SB0 + C::slot_off(k >> 2) + (k & 3) * 256, 128, 1024); }
template <int N>
__device__ __forceinline__ void store_pair(const float (&d)[N], int j0, int j1, uint32_t a) {
  stsm4(a, pack_bf16(d[4 * j0], d[4 * j0 + 1]), pack_bf16(d[4 * j0 + 2], d[4 * j0 + 3]), pack_bf16(d[4 * j1], d[4 * j1 + 1]), pack_bf16(d[4 * j1 + 2], d[4 * j1 + 3]));
}
__device__ __forceinline__ uint32_t tile_lane(int tid) { return (((tid >> 4) & 6) + ((tid >> 3) & 1)) * 1280 + (tid & 7) * 16; }
__device__ __forceinline__ void load_chunk(const CUtensorMap& tmX, uint32_t sb, int b, int c, int off, int bar) {
  tma3d_mc(sb + off, &tmX, c * 256, 4 * b, 0, sb + bar);
}
__device__ __forceinline__ void arrive_all(uint32_t sb, int bar, int i) {
  asm volatile("{.reg .pred p; .reg .b32 a; setp.lt.u32 p,%1,3; @p mapa.shared::cluster.u32 a,%0,%1; @p mbarrier.arrive.shared::cluster.b64 _,[a];}"
               ::"r"(sb + bar), "r"(i) : "memory");
}
static void fill_descs(ChainArgs& a) {
  using namespace C;
  for (int k = 0; k < 40; k++) a.td[k] = tdesc(k);
  for (int k = 0; k < 40; k++) { a.rd[k] = rdesc(k); a.kd[k] = wdesc(OFF_WK + k * 2048); a.od[k] = wdesc(wo_off(k >> 2) + (k & 3) * 2048); }
  for (int k = 0; k < 4; k++) a.kd[40 + k] = wdesc(OFF_WXQ + k * 2048);
  for (int k = 0; k < 12; k++) a.gd[k] = mkdesc_ns(SB0 + OFF_OG + k * 512, 256, 128);
  for (int k = 0; k < 8; k++) {
    a.sd[2 * k] = mkdesc_ns(SB0 + OFF_QT + (k >> 1) * 2560 + (k & 1) * 256, 1280, 128);
    a.sd[2 * k + 1] = mkdesc_ns(SB0 + OFF_KT + (k >> 1) * 2560 + (k & 1) * 640, 1280, 128);
  }
  for (int k = 0; k < 5; k++) a.vd[k] = mkdesc_ns(SB0 + OFF_VT + k * 256, 128, 1280);
  const int grp[4] = {0, 9, 1, 5};
  for (int k = 0; k < 12; k++) a.pd[k] = mkdesc_ns(SB0 + OFF_P + grp[k / 3] * 768 + (k % 3) * 256, 128, 768);
}

#define B1T 2
#define RIDL 0
#define S9E 1
#define F2K 16
#define PVE 0
#define QGA 3
#define NOX 0
#define VD 0
#define TD(k) a.td[k]
#define RD(k) a.rd[k]
template <int N, typename F>
__device__ __forceinline__ void k_chunk(F mma, float (&d)[N], uint32_t alo, uint32_t blo, uint32_t bhi) {
  wg_fence();
#pragma unroll
  for (int k = 0; k < 4; k++) mma(d, desc2(alo + k * 128, (uint32_t)(wdesc(0) >> 32)), desc2(blo + k * 16, bhi), 1);
  wg_commit();
}

__device__ __forceinline__ uint32_t quad_max_h2(uint32_t m) {
  const uint32_t a = __shfl_xor_sync(0xffffffffu, m, 1), b = __shfl_xor_sync(0xffffffffu, m, 2), c = __shfl_xor_sync(0xffffffffu, m, 3);
  return max_h2(max_h2(m, a), max_h2(b, c));
}
__device__ __forceinline__ uint32_t diag_mask(int lane) {
  const int dg = (lane >> 2) - 2 * (lane & 3);
  return dg >= 1 ? 0u : dg == 0 ? 0xFC000000u : 0xFC00FC00u;
}
__device__ __forceinline__ float quad_sum(float m) {
  const float a = __shfl_xor_sync(0xffffffffu, m, 1), b = __shfl_xor_sync(0xffffffffu, m, 2), c = __shfl_xor_sync(0xffffffffu, m, 3);
  return (m + a) + (b + c);
}
__device__ __forceinline__ float rcp(float x) { float y; asm("rcp.approx.ftz.f32 %0,%1;" : "=f"(y) : "f"(x)); return y; }
__device__ __forceinline__ void p_store(uint32_t base, bool layer, int lane, uint32_t p0, uint32_t p1, uint32_t p2, uint32_t p3, uint32_t p4) {
  stsm4(base + (layer ? 128 : 0) + lane * 16, p0, p1, p2, p3);
  stsm2(base + ((lane & 8) ? (layer ? 0 : 640) : (layer ? 640 : 512)) + (lane & 7) * 16, p4, 0u);
}

__device__ __forceinline__ void chain_q(const CUtensorMap& tmWk, const CUtensorMap& tmWo, const CUtensorMap& tmX, const ChainArgs& a,
                                        const uint32_t sb, const int tid0, const int cta, const int rank) {
  using namespace C;
  asm volatile("setmaxnreg.inc.sync.aligned.u32 208;");
  int left = SPIN_BUDGET;
  uint32_t wf[39][4];
  mbar_wait(sb + BAR_W1, 0, left);
  PTS(4);
  load_wfrags<39>(wf, sb + STAGE_Q, tid0 >> 5, tid0 & 31);
  cluster_sync();
  PTS(5);
  const uint32_t qa = sb + OFF_QT + tile_lane(tid0) + ((tid0 & 16) ? 9 * 128 : 0);
  const int dq = (tid0 & 16) ? -128 : 128;
  const int warp = __shfl_sync(0xffffffffu, tid0 >> 5, 0);
  if (tid0 < 4) mbar_expect_tx(sb + BAR_F0 + 8 * tid0, tid0 == 3 ? 20480 : (3 + (tid0 >> 1)) * SLOT);
  if (tid0 == 0) {
    const int head = cta / 3, col = head * DH + rank * 64;
    mbar_expect_tx(sb + BAR_W2, 32768);
    for (int i = 6; i < 10; i++) tma2d(sb + OFF_WK + i * 8192, &tmWk, col, i * 64, sb + BAR_W2);
    load_chunk(tmX, sb, 0, rank, slot_off(rank), BAR_F0);
    mbar_expect_tx(sb + BAR_W3, 81920);
    for (int u = 9; u >= 0; u--) {
      const int n = u ? (u - 1) / 3 : 0;
      tma2d(sb + wo_off(u), &tmWo, u == 0 ? 576 : (3 * rank + (u - 1) % 3) * 64, head * DH + ((rank + 3 - n) % 3) * 64, sb + BAR_W3);
    }
  }
  __syncwarp();

  for (int b = 0; b < NS; b++) {
    const int ph = b & 1;
    {
      float d[24];
      mbar_wait(sb + BAR_F0, ph, left);
      if (b > 0) bar_sync(NB_GO, 256);
      TSB(b, 16);
      wg_fence();
#pragma unroll
      for (int k = 0; k < 12; k++) wgmma_rs48(d, wf[k], TD(k), k);
      wg_commit();
      mbar_wait(sb + BAR_F1, ph, left);
      wg_fence();
#pragma unroll
      for (int k = 12; k < F2K; k++) wgmma_rs48(d, wf[k], TD(k), 1);
      wg_commit();
      wg_wait<1>();
      arrive_all(sb, BAR_RE, tid0 - 32);
      if (warp == 0) {
        mbar_wait(sb + BAR_VF, ph, left);
        if (elect()) {
          load_chunk(tmX, sb, b, 6 + rank, slot_off(6) + rank * SLOT, BAR_F2);
          if (rank == 0) load_chunk(tmX, sb, b, 9, slot_off(9), BAR_F2);
        }
        TS(b, 21);
      }
      wg_fence();
#pragma unroll
      for (int k = F2K; k < 24; k++) wgmma_rs48(d, wf[k], TD(k), 1);
      if (RIDL == 0 && warp == 0 && rank) {
        mbar_wait(sb + BAR_RE, ph, left);
        if (elect()) bulk_g2s_mc(sb + OFF_R + (1 + rank) * 10240, a.xn + (size_t)(4 * b + 3 + (rank - 1) * (256 - 4 * LAG)) * 10240, 10240, sb + BAR_RID);
      }
      mbar_wait(sb + BAR_F2, ph, left);
      if (RIDL == 1 && warp == 0 && rank) {
        mbar_wait(sb + BAR_RE, ph, left);
        if (elect()) bulk_g2s_mc(sb + OFF_R + (1 + rank) * 10240, a.xn + (size_t)(4 * b + 3 + (rank - 1) * (256 - 4 * LAG)) * 10240, 10240, sb + BAR_RID);
      }
      wg_fence();
#pragma unroll
      for (int k = 24; k < 39; k++) wgmma_rs48(d, wf[k], TD(k), 1);
      wgmma_ts48(d, a.kd[40], TD(39), 1);
      wg_commit();
      wg_wait<0>();
      TS(b, 17);
      bar_arrive(NB_BQ, 256);
      arrive_all(sb, BAR_XE, tid0 - 32);
      bar_sync(NB_BV, 256);
#pragma unroll
      for (int j = 0; j < 3; j++) store_pair(d, j, j + 3, qa + (4 - j) * dq);
    }
    {
      float d[16];
      bar_sync(NB_M2, 256);
      TSB(b, 18);
      wg_fence();
#pragma unroll
      for (int k = 0; k < 39; k++) wgmma_rs32(d, wf[k], RD(k), k);
      wgmma_ts32(d, a.kd[40], RD(39), 1);
      wg_commit();
      wg_wait<0>();
      TS(b, 19);
      store_pair(d, 0, 1, qa);
      store_pair(d, 2, 3, qa + dq);
      fence_async();
      bar_arrive(NB_QK, 384);
    }
    const int bn = b + 1;
    if (tid0 < 4) mbar_expect_tx(sb + BAR_F0 + 8 * tid0, tid0 == 3 ? 20480 : (3 + (tid0 >> 1)) * SLOT);
    {
      const int lane = fresh(tid0) & 31;
      const bool up = warp >= 2, outer = warp == 0 || warp == 3;
      const uint32_t xo = xl_off(warp), ob = sb + xo + lane * 16;
      const uint32_t dm = diag_mask(lane);
      if (warp == 0) {
        bar_sync(NB_S, 288);
        if (bn < NS && elect()) {
          mbar_expect_tx(sb + BAR_ROT, 16384);
          bulk_g2s(sb + wo_off(0), a.rot + (size_t)cta * 32768, 16384, sb + BAR_ROT);
        }
        __syncwarp();
      }
      bar_sync(NB_X + warp, 64);
      fence_async();
      if (elect()) {
        const uint32_t r1 = mapa(sb, (rank + 1) % 3), r2 = mapa(sb, (rank + 2) % 3), n = outer ? 640 : 1152;
        bulk_s2c(r1 + xo + 3584, sb + xo + 7168, n, r1 + BAR_X + 8 + 8 * warp);
        bulk_s2c(r2 + xo, sb + xo + 7168, n, r2 + BAR_X + 8 + 8 * warp);
      }
      __syncwarp();
      mbar_wait(sb + BAR_X + 8 + 8 * warp, ph, left);
      {
        float z[10];
        const uint4 s = lds128(ob + 7168), u = lds128(ob), v = lds128(ob + 3584);
        const uint32_t ts = lds32(ob + 7168 + 512 - lane * 12), tu = lds32(ob + 512 - lane * 12), tv = lds32(ob + 3584 + 512 - lane * 12);
        const uint32_t h[5] = {add_h2(add_h2(s.x, u.x), v.x), add_h2(add_h2(s.y, u.y), v.y), add_h2(add_h2(add_h2(s.z, outer ? 0u : dm), u.z), v.z),
                               add_h2(add_h2(s.w, u.w), v.w), add_h2(add_h2(add_h2(ts, dm), tu), tv)};
        const uint32_t ma = max_h2(max_h2(h[0], h[1]), h[2]), mb = max_h2(h[3], h[4]);
        uint32_t m = max_h2(__byte_perm(ma, mb, 0x5410), __byte_perm(ma, mb, 0x7632));
        if (outer) m = max_h2(m, __byte_perm(m, m, 0x1032));
        const float2 mf = unpack_h2(quad_max_h2(m));
        const float m0 = -SCL * mf.x, m1 = -SCL * mf.y;
#pragma unroll
        for (int j = 0; j < 5; j++) {
          const float2 f = unpack_h2(h[j]);
          z[2 * j] = ex2(fmaf(f.x, SCL, j < 3 ? m0 : m1)); z[2 * j + 1] = ex2(fmaf(f.y, SCL, j < 3 ? m0 : m1));
        }
        float s0 = ((z[0] + z[1]) + (z[2] + z[3])) + (z[4] + z[5]), s1 = (z[6] + z[7]) + (z[8] + z[9]);
        if (outer) s0 = s1 = s0 + s1;
        s0 += __shfl_xor_sync(0xffffffffu, s0, 1); s1 += __shfl_xor_sync(0xffffffffu, s1, 1);
        s0 = rcp(s0 + __shfl_xor_sync(0xffffffffu, s0, 2)); s1 = rcp(s1 + __shfl_xor_sync(0xffffffffu, s1, 2));
        const uint32_t p3 = pack_bf16(z[6] * s1, z[7] * s1), p4 = pack_bf16(z[8] * s1, z[9] * s1);
        p_store(sb + OFF_P + (2 * warp + (up ? 2 : 1)) * 768, up, lane, pack_bf16(z[0] * s0, z[1] * s0), pack_bf16(z[2] * s0, z[3] * s0), pack_bf16(z[4] * s0, z[5] * s0),
                outer ? p3 : 0u, outer ? p4 : 0u);
        if (!outer) p_store(sb + OFF_P + (up ? 4 * 768 : 5 * 768), !up, lane, p3, p4, 0u, 0u, 0u);
      }
      fence_async();
      bar_arrive(NB_V, 384);
      TS(b, 31);
    }
  }
  if (left <= 0) g_err = 1;
}

__device__ __forceinline__ void chain_v(const ChainArgs& a, const uint32_t sb, const int tid0, const int cta, const int rank) {
  using namespace C;
  asm volatile("setmaxnreg.inc.sync.aligned.u32 224;");
  int left = SPIN_BUDGET;
  uint32_t wf[37][4];
  mbar_wait(sb + BAR_W1, 0, left);
  load_wfrags<37>(wf, sb + STAGE_V + 3 * 2048, tid0 >> 5, tid0 & 31);
  cluster_sync();
  mbar_wait(sb + BAR_W2, 0, left);
  uint32_t mo = (24 * rank + (tid0 >> 4)) * MAIL_UNIT + (cta / 24) * 8192 + ((cta / 3) & 7) * 256 + (tid0 & 15) * 16;
  const int blk9 = cta / 24 + (cta % 24 < 16 ? 0 : 4);
  uint32_t mo9 = (72 + (tid0 >> 3)) * MAIL_UNIT + blk9 * 8192 + ((cta % 24) & 15) * 128 + (tid0 & 7) * 16;
#pragma unroll 1
  for (int i = 0; i < 4; i++) {
    const uint32_t* p = &g_sel[i < 3 ? 24 * rank + 8 * i + (tid0 >> 4) : 72 + (tid0 >> 3)];
    uint32_t v;
    while (__any_sync(0xffffffffu, (v = ld_acquire(p)) == 0) && (left -= 16) > 0) {}
    v = (v >> (i < 3 ? cta / 24 : blk9)) & 1;
    if (i == 0) mo |= v * 0x1003;
    else if (i < 3) mo ^= v * i;
    else mo9 |= v << 12;
  }
  const uint32_t ka = sb + OFF_KT + tile_lane(tid0) + ((tid0 & 16) ? 640 : 0);
  const int warp = __shfl_sync(0xffffffffu, tid0 >> 5, 0);

  for (int b = 0; b < NS; b++) {
    const int ph = b & 1;
    {
      float dv[24], dk[24];
#define VK(K0, K1)                                                   \
  wg_fence();                                                        \
  _Pragma("unroll") for (int k = K0; k < K1; k++) {                  \
    if (k < 3) wgmma_ts48(dv, a.kd[41 + k], TD(k), k);               \
    else wgmma_rs48(dv, wf[k - 3], TD(k), 1);                        \
    wgmma_ts48(dk, a.kd[k], TD(k), k);                               \
  }                                                                  \
  wg_commit();
      mbar_wait(sb + BAR_F0, ph, left);
      TSB(b, 22);
      VK(0, 12)
      mbar_wait(sb + BAR_F1, ph, left);
      VK(12, 15)
      wg_wait<1>();
      arrive_all(sb, BAR_RE, tid0);
      VK(15, 24)
      TS(b, 23);
      mbar_wait(sb + BAR_F2, ph, left);
      VK(24, 27)
      wg_wait<1>();
      bar_arrive(NB_BV, 256);
      VK(27, 40)
#undef VK
      wg_wait<0>();
      TS(b, 24);
      arrive_all(sb, BAR_XE, tid0);
      bar_sync(NB_BQ, 256);
#pragma unroll
      for (int j = 0; j < 3; j++) { store_pair(dk, j, j + 3, ka + (1 + j) * 128); store_pair(dv, j, j + 3, ka + 10240 + (1 + j) * 128); }
    }
    const bool succ = b + 1 < NS;
    {
      float d[16] = {};
      bar_sync(NB_M, 256);
#pragma unroll 1
      for (int c = 0; c < a.ten; c++) k_chunk(wgmma_ts32, d, (uint32_t)wdesc(OFF_WK) + c * 512, (uint32_t)rdesc(0) + c * 64, (uint32_t)(rdesc(0) >> 32));
      wg_wait<0>();
      TS(b, 25);
      store_pair(d, 0, 1, ka);
      store_pair(d, 2, 3, ka + 4 * 128);
      fence_async();
      bar_arrive(NB_QK, 384);
      bar_sync(NB_S, 288);
      wg_fence();
#pragma unroll
      for (int k = 0; k < 40; k++) {
        if (k < 3) wgmma_ts32(d, a.kd[41 + k], RD(k), k);
        else wgmma_rs32(d, wf[k - 3], RD(k), 1);
      }
      wg_commit();
      wg_wait<0>();
      TS(b, 26);
      arrive_all(sb, BAR_OE, tid0 - 32);
      if (warp == 0 && succ && elect()) {
        mbar_expect_tx(sb + BAR_OG, 2048);
        mbar_expect_tx(sb + BAR_OG2, 16384 + 2048);
        bulk_g2s(sb + wo_off(8), a.rot + (size_t)cta * 32768 + 16384, 16384, sb + BAR_OG2);
      }
      __syncwarp();
      store_pair(d, 0, 1, ka + 10240);
      store_pair(d, 2, 3, ka + 10240 + 4 * 128);
      fence_async();
      if (!succ) { bar_arrive(NB_V, 384); break; }
      mbar_wait(sb + BAR_ROT, ph, left);
    }
    bar_sync(NB_P, 192);
    TSB(b, 27);
    {
      float o0[4], o1[4];
      wg_fence();
#pragma unroll
      for (int q = 0; q < 3; q++) {
        wgmma_ss8(o0, a.vd[q], a.pd[q], q);
        wgmma_ss8(o1, a.vd[2 + q], a.pd[3 + q], q);
      }
      wg_commit();
      wg_wait<0>();
      TS(b, 6);
      stsm4(sb + OFF_OG + tid0 * 16, pack_bf16(o0[0], o0[1]), pack_bf16(o1[0], o1[1]), pack_bf16(o0[2], o0[3]), pack_bf16(o1[2], o1[3]));
      fence_async();
    }
    bar_sync(NB_O, 160);
    TSB(b, 7);
    {
      float acc[4][8];
      wg_fence();
#pragma unroll
      for (int kk = 0; kk < 4; kk++) wgmma_tt16(acc[3], a.od[kk], a.gd[kk], kk);
#pragma unroll
      for (int i = 0; i < 3; i++)
#pragma unroll
        for (int kk = 0; kk < 4; kk++) {
          wgmma_tt16(acc[i], a.od[4 + 4 * i + kk], a.gd[kk], kk);
          if (i != 1 && kk == 3) wg_commit();
        }
      wg_wait<1>();
      arrive_all(sb, BAR_RQ, tid0);
      uint8_t* mb = a.mail + ph * 2048;
      const uint32_t tag = (b >> 1) & 1, radd = tag ? 0u : 0x10000u;
#define TAGPACK(LO, HI) (__byte_perm(((__float_as_uint(LO) + radd) & 0xFFFE0000u) | (tag << 16), pack_bf16(0.f, HI), 0x7632))
#define SEND(O, I) st_msg16(mb + (O), TAGPACK(acc[I][0], acc[I][2]), pack_bf16(acc[I][1], acc[I][3]), \
                            pack_bf16(acc[I][4], acc[I][6]), pack_bf16(acc[I][5], acc[I][7]))
      if (S9E == 1) { SEND(mo9, 3); __syncwarp(); }
      mbar_wait(sb + BAR_OG, ph, left);
      if (S9E == 2) { SEND(mo9, 3); __syncwarp(); }
      TS(b, 8);
      wg_fence();
#pragma unroll
      for (int k = 0; k < 12; k++) wgmma_tt16(acc[k >> 2], a.od[16 + k], a.gd[4 + (k & 3)], 1);
      mbar_wait(sb + BAR_OG2, ph, left);
      TS(b, 29);
      wg_fence();
#pragma unroll
      for (int k = 0; k < 12; k++) {
        wgmma_tt16(acc[k >> 2], a.od[28 + k], a.gd[8 + (k & 3)], 1);
        if ((k & 3) == 3) wg_commit();
      }
      const uint32_t o = mo & ~3u;
      if (!S9E) { SEND(mo9, 3); __syncwarp(); }
      wg_wait<2>();
      SEND(o, 0);
      __syncwarp();
      wg_wait<1>();
      SEND((o ^ ((mo & 1) << 12)) + 8 * MAIL_UNIT, 1);
      __syncwarp();
      if (QGA == 2) bar_arrive(NB_GO, 256);
      wg_wait<0>();
      if (QGA == 3) bar_arrive(NB_GO, 256);
      TS(b, 30);
      if (PVE) bar_arrive(NB_V, 384);
      SEND((o ^ ((mo & 2) << 11)) + 16 * MAIL_UNIT, 2);
      if (!PVE) bar_arrive(NB_V, 384);
      if (QGA == 0) bar_arrive(NB_GO, 256);
#undef SEND
#undef TAGPACK
      TS(b, 9);
      arrive_all(sb, BAR_RF, tid0 - 96);
      if (VD) { const uint32_t t0 = clk32(); while (clk32() - t0 < VD) {} }
    }
  }
  if (left <= 0) g_err = 2;
}

__device__ __forceinline__ void sum_msg(float (&e)[8], const uint4& a, const uint4& b, const uint4& c, const uint4& d) {
  e[0] = (bf_lo(a.x) + bf_lo(b.x)) + (bf_lo(c.x) + bf_lo(d.x)); e[1] = (bf_hi(a.x) + bf_hi(b.x)) + (bf_hi(c.x) + bf_hi(d.x));
  e[2] = (bf_lo(a.y) + bf_lo(b.y)) + (bf_lo(c.y) + bf_lo(d.y)); e[3] = (bf_hi(a.y) + bf_hi(b.y)) + (bf_hi(c.y) + bf_hi(d.y));
  e[4] = (bf_lo(a.z) + bf_lo(b.z)) + (bf_lo(c.z) + bf_lo(d.z)); e[5] = (bf_hi(a.z) + bf_hi(b.z)) + (bf_hi(c.z) + bf_hi(d.z));
  e[6] = (bf_lo(a.w) + bf_lo(b.w)) + (bf_lo(c.w) + bf_lo(d.w)); e[7] = (bf_hi(a.w) + bf_hi(b.w)) + (bf_hi(c.w) + bf_hi(d.w));
}
__device__ __forceinline__ void publish(const ChainArgs& a, int b, int warp, uint32_t src, uint32_t o) {
  const uint32_t off = (o >> 12) * 8192 + (o & 4095);
  uint32_t v = SENT;
  if (warp < 2) {
    const uint2 p = lds64(src), q = lds64(src + 256), r = lds64(src + 512), s = lds64(src + 768);
    v = pack_bf16((__uint_as_float(p.x) + __uint_as_float(q.x)) + (__uint_as_float(r.x) + __uint_as_float(s.x)),
                  (__uint_as_float(p.y) + __uint_as_float(q.y)) + (__uint_as_float(r.y) + __uint_as_float(s.y)));
    if (b + 1 == LAG && o >= 10240) v = ld_relaxed(a.mbuf + 2 * 40960 + off);
  }
  uint8_t* dst = a.mbuf + (((b + 1 + (warp >> 1)) & 1) * 40960 + off);
  st_relaxed(dst, v);
  st_relaxed(dst + 4096, v);
}

__device__ __forceinline__ void store_o(const ChainArgs& a, const uint4 (&ok)[4], int b, int cta, int tid) {
  uint8_t* p = a.oimg + (uint32_t)(((b & 7) * 192 + cta) * 4096 + (tid >> 5) * 1024 + ((tid ^ ((tid >> 3) & 3)) & 31) * 16);
  *reinterpret_cast<uint4*>(p) = ok[0]; *reinterpret_cast<uint4*>(p + 512) = ok[1];
  *reinterpret_cast<uint4*>(p + 96 * 4096) = ok[2]; *reinterpret_cast<uint4*>(p + 96 * 4096 + 512) = ok[3];
}

__device__ __forceinline__ void fetch_rows(const ChainArgs& a, uint32_t sb, int warp, int slot, uint32_t al) {
  using namespace C;
  const uint8_t* src = a.mbuf + slot * 40960;
  mbar_expect_tx(sb + BAR_M + 8 * warp, 5120);
  bulk_g2s(sb + OFF_R + warp * 4096, src + (warp * 8192 + ((al >> warp) & 1) * 4096), 4096, sb + BAR_M + 8 * warp);
  bulk_g2s(sb + OFF_R + 16384 + warp * 1024, src + (32768 + (al & 16) * 256 + warp * 1024), 1024, sb + BAR_M + 8 * warp);
}

__device__ __forceinline__ void chain_a(const CUtensorMap& tmX, const ChainArgs& a, const uint32_t sb, const int tid0, const int cta, const int rank, const int unit) {
  using namespace C;
  asm volatile("setmaxnreg.dec.sync.aligned.u32 72;");
  int left = SPIN_BUDGET;
  const int warp = __shfl_sync(0xffffffffu, tid0 >> 5, 0);
  uint32_t rsel;
  asm volatile("ld.shared.u8 %0,[%1];" : "=r"(rsel) : "r"(sb + OFF_SEL + (tid0 & 31)) : "memory");
  rsel = __ballot_sync(0xffffffffu, rsel) & 0x3ffff;
  if (unit < NUNIT) {
#pragma unroll 1
    for (int i = tid0; i < (unit < 72 ? 1024 : 2048); i += 128)
      *reinterpret_cast<uint4*>(a.mail + (size_t)unit * MAIL_UNIT + (i >> 8) * 8192 + ((rsel >> (10 + (i >> 8))) & 1) * 4096 + (i & 255) * 16) = make_uint4(SENT, SENT, SENT, SENT);
    bar_sync(NB_MR, 128);
    if (tid0 == 0) asm volatile("st.release.gpu.global.b32 [%0],%1;" ::"l"(&g_sel[unit]), "r"(256 | (rsel >> 10)) : "memory");
  }
  cluster_sync();
  mbar_wait(sb + BAR_W3, 0, left);
  PTS(6);
#pragma unroll 1
  for (int it = 2559 - tid0; it >= 0; it -= 128) {
    const int row = it >> 2, q = it & 3;
    const uint32_t base = sb + (row < 384 ? OFF_WO : row < 512 ? wo_off(0) - 6 * 8192 : wo_off(8) - 8 * 8192) + row * 128;
    const uint32_t a0 = base + (((2 * q) ^ (row & 7)) << 4), a1 = base + (((2 * q + 1) ^ (row & 7)) << 4);
    const uint4 u = lds128(a0), v = lds128(a1);
    sts128(a0, make_uint4(__byte_perm(u.x, u.y, 0x5410), __byte_perm(u.z, u.w, 0x5410), __byte_perm(v.x, v.y, 0x5410), __byte_perm(v.z, v.w, 0x5410)));
    sts128(a1, make_uint4(__byte_perm(u.x, u.y, 0x7632), __byte_perm(u.z, u.w, 0x7632), __byte_perm(v.x, v.y, 0x7632), __byte_perm(v.z, v.w, 0x7632)));
    if (row >= 384 && row < 416) {
      fence_async();
      bar_sync(NB_MR, 128);
      if (tid0 == 0) {
        bulk_s2g(a.rot + (size_t)cta * 32768, sb + wo_off(0), 16384);
        bulk_s2g(a.rot + (size_t)cta * 32768 + 16384, sb + wo_off(8), 16384);
        bulk_commit();
      }
    }
  }
  fence_async();
  if (tid0 == 0) bulk_wait();
  bar_sync(NB_MR, 128);
  arrive_all(sb, BAR_RF, tid0);
  arrive_all(sb, BAR_VF, tid0);
  __syncwarp();
  mbar_wait(sb + BAR_RF, 0, left);
  if (tid0 == 0) load_chunk(tmX, sb, 0, 3 + rank, slot_off(3) + rank * SLOT, BAR_F1);
  __syncwarp();
  uint4 ok[4] = {};
  uint32_t mph = 0;
  uint32_t mo = (unit < NUNIT ? unit : NUNIT) * MAIL_UNIT + warp * 8192 + ((rsel >> (10 + warp)) & 1) * 4096 + (tid0 & 31) * 16;
  const uint32_t mo2 = 32768 + (((rsel >> (10 + warp)) ^ (rsel >> (14 + warp))) & 1) * 4096;
  DUR(1);
  __syncwarp();
  if (elect()) fetch_rows(a, sb, warp, 2, 0);
  __syncwarp();

  for (int b = 0; b < NS; b++) {
    const int ph = b & 1;
    {
      const int lane = fresh(tid0) & 31;
      const uint32_t va = sb + OFF_R + lane * 32 + (lane & 28);
      int n = 0;
      if (OSP == 1 && b > 0) store_o(a, ok, b - 1, cta, fresh(tid0));
      mbar_wait(sb + BAR_RID, ph, left);
#pragma unroll 1
      while (true) {
        mbar_wait(sb + BAR_M + 8 * warp, mph, left);
        if (n == 0) TS(b, 13);
        const uint32_t v0 = lds32(va + warp * 4096), v1 = lds32(va + warp * 4096 + 1024), v2 = lds32(va + warp * 4096 + 2048), v3 = lds32(va + warp * 4096 + 3072);
        const uint32_t v4 = lds32(va + 16384 + warp * 1024), v5 = lds32((va ^ 8) + (warp == 2 ? 9216 : 16384 + warp * 1024));
        mph ^= 1;
        n++;
        if (!__any_sync(0xffffffffu, max(max(max(v0, v1), v2), max(max(v3, v4), v5)) == SENT) || (left -= 16) <= 0) break;
        if (elect()) fetch_rows(a, sb, warp, ph, rsel >> (5 * ph));
        __syncwarp();
      }
      bar_arrive(NB_M, 256);
      bar_arrive(NB_M2, 256);
      TS(b, 0);
      TSV(b, 14, n);
    }
    if (b > 0) {
      if (OSP == 0) store_o(a, ok, b - 1, cta, fresh(tid0));
      bar_sync(NB_MR, 128);
      if (warp == 1 && elect()) cnt_signal(&g_cnt[CN_O][b - 1][(cta >> 4) * 32]);
      __syncwarp();
    }
    if (tid0 < 5) mbar_expect_tx(sb + BAR_X + 8 * tid0, tid0 == 0 ? 2560 : (tid0 & 2) ? 2304 : 1280);
    if ((tid0 & 31) == 8) mbar_expect_tx(sb + BAR_M + 8 * warp, 5120);
    TS_FLUSH(b - 1);
    mbar_wait(sb + BAR_XE, ph, left);
    {
      const int lane = fresh(tid0) & 31, w = fresh(warp);
      const bool up = w >= 2, outer = w == 0 || w == 3;
      const uint32_t r1 = mapa(sb, (rank + 1) % 3), r2 = mapa(sb, (rank + 2) % 3);
      const uint32_t pa = OFF_P + (2 * w + (up ? 3 : 0)) * 768;
      const uint32_t ob = xl_off(w) + lane * 16;
      const uint32_t oa = outer ? pa + lane * 16 : ob + 640, oc = outer ? OFF_XM + (up ? 640 : 0) + lane * 16 : ob + 640 + 3584;
      float x0[20], x1[20];
      bar_sync(NB_QK, 384);
      TSB(b, 1);
      wg_fence();
#pragma unroll
      for (int kk = 0; kk < 4; kk++) {
        wgmma_tt40(x0, a.sd[4 * kk], a.sd[4 * kk + 1], kk);
        wgmma_tt40(x1, a.sd[4 * kk + 2], a.sd[4 * kk + 3], kk);
      }
      wg_commit();
      wg_wait<0>();
      bar_arrive(NB_S, 288);
      TS(b, 2);
      uint32_t h[5], z[5];
#pragma unroll
      for (int j = 0; j < 5; j++) h[j] = pack_h2(up ? x1[4 * j + 2] : x0[4 * j], up ? x1[4 * j + 3] : x0[4 * j + 1]);
      if (outer) {
        st_async4(r1 + oc, h[0], h[1], h[2], h[3], r1 + BAR_X);
        st_async4(r2 + oa, h[0], h[1], h[2], h[3], r2 + BAR_X);
        st_async1(r1 + oc + 512 - lane * 12, h[4], r1 + BAR_X);
        st_async1(r2 + oa + 512 - lane * 12, h[4], r2 + BAR_X);
      } else {
        sts128(sb + oa + 7168, make_uint4(h[0], h[1], h[2], h[3]));
      }
#pragma unroll
      for (int j = 0; j < 5; j++) z[j] = pack_h2(up ? x1[4 * j] : x0[4 * j + 2], up ? x1[4 * j + 1] : x0[4 * j + 3]);
      if (!outer) {
#pragma unroll
        for (int j = 0; j < 2; j++) z[3 + j] = pack_h2(up ? x0[4 * j] : x1[4 * j + 2], up ? x0[4 * j + 1] : x1[4 * j + 3]);
        h[3] = add_h2(h[3], diag_mask(lane));
      }
      sts128(sb + ob + 7168, make_uint4(z[0], z[1], z[2], z[3]));
      sts32(sb + ob + 7168 + 512 - lane * 12, z[4]);
      bar_arrive(NB_X + w, 64);
      TS(b, 3);
      mbar_wait(sb + BAR_X + (outer ? 0 : 8 + 8 * w), ph, left);
      TS(b, 4);
      {
        const uint4 u = lds128(sb + oa), v = lds128(sb + oc);
        const uint32_t tu = lds32(sb + oa + 512 - lane * 12), tv = lds32(sb + oc + 512 - lane * 12);
        h[0] = add_h2(add_h2(h[0], u.x), v.x); h[1] = add_h2(add_h2(h[1], u.y), v.y); h[2] = add_h2(add_h2(h[2], u.z), v.z);
        h[3] = add_h2(add_h2(h[3], u.w), v.w); h[4] = outer ? add_h2(add_h2(h[4], tu), tv) : 0xFC00FC00u;
        const float2 mf = unpack_h2(quad_max_h2(max_h2(max_h2(max_h2(h[0], h[1]), max_h2(h[2], h[3])), h[4])));
        const float m = -SCL * fmaxf(mf.x, mf.y);
        float y[10];
#pragma unroll
        for (int j = 0; j < 5; j++) { const float2 f = unpack_h2(h[j]); y[2 * j] = ex2(fmaf(f.x, SCL, m)); y[2 * j + 1] = ex2(fmaf(f.y, SCL, m)); }
        const float r = rcp(quad_sum(((y[0] + y[1]) + (y[2] + y[3])) + ((y[4] + y[5]) + (y[6] + y[7])) + (y[8] + y[9])));
        p_store(sb + pa, up, lane, pack_bf16(y[0] * r, y[1] * r), pack_bf16(y[2] * r, y[3] * r), pack_bf16(y[4] * r, y[5] * r),
                pack_bf16(y[6] * r, y[7] * r), pack_bf16(y[8] * r, y[9] * r));
      }
      fence_async();
      if (outer) bar_arrive(NB_P, 192);
      TS(b, 5);
    }
    const int bn = b + 1;
    if (warp == 0 && bn < NS) {
      if (!NOX && bn >= LAG) {
        while (__any_sync(0xffffffffu, ld_acquire(&g_cnt[CN_X][bn - LAG][0]) < 4) && (left -= 16) > 0) {}
        fence_async_all();
      }
      mbar_wait(sb + BAR_OE, ph, left);
      if (elect()) load_chunk(tmX, sb, bn, rank, slot_off(0) + rank * SLOT, BAR_F0);
      TS(b, 20);
      mbar_wait(sb + BAR_RQ, ph, left);
      if (elect()) load_chunk(tmX, sb, bn, 3 + rank, slot_off(3) + rank * SLOT, BAR_F1);
      __syncwarp();
    }
    if (warp == 3 && bn < NS) {
      const uint32_t r1 = mapa(sb, (rank + 1) % 3), r2 = mapa(sb, (rank + 2) % 3);
      mbar_wait(sb + BAR_OE, ph, left);
      bar_sync(NB_O, 160);
      if (elect()) {
        bulk_s2c(r1 + OFF_OG + 2048, sb + OFF_OG, 2048, r1 + BAR_OG);
        bulk_s2c(r2 + OFF_OG + 4096, sb + OFF_OG, 2048, r2 + BAR_OG2);
      }
      __syncwarp();
    }
    uint4 x[6];
    bar_sync(NB_V, 384);
    {
      float o0[16], o1[16];
      wg_fence();
#pragma unroll
      for (int q = 0; q < 3; q++) {
        wgmma_ss32(o0, a.vd[q], a.pd[6 + q], q);
        wgmma_ss32(o1, a.vd[2 + q], a.pd[9 + q], q);
      }
      wg_commit();
      if (bn < NS) {
        if (unit < 72) mbar_wait(sb + BAR_RF, ph ^ 1, left);
        if (QGA == 1) bar_arrive(NB_GO, 256);
        if (B1 && unit < 72 && (unit >> 3) % 3 >= B1T) { const uint32_t t0 = clk32(); while (clk32() - t0 < B1) {} }
      }
      ld_msg16x4(x, a.mail + mo);
      __syncwarp();
      wg_wait<0>();
      arrive_all(sb, BAR_VF, tid0);
#pragma unroll
      for (int h = 0; h < 2; h++) {
        ok[h] = make_uint4(pack_bf16(o0[12 + 2 * h], o0[13 + 2 * h]), pack_bf16(o0[8 + 2 * h], o0[9 + 2 * h]),
                           pack_bf16(o0[4 + 2 * h], o0[5 + 2 * h]), pack_bf16(o0[2 * h], o0[1 + 2 * h]));
        ok[2 + h] = make_uint4(pack_bf16(o1[2 * h], o1[1 + 2 * h]), pack_bf16(o1[4 + 2 * h], o1[5 + 2 * h]),
                               pack_bf16(o1[8 + 2 * h], o1[9 + 2 * h]), pack_bf16(o1[12 + 2 * h], o1[13 + 2 * h]));
      }
      TS(b, 28);
    }
    if (b + 1 == NS) break;
    {
      const int lane = fresh(tid0) & 31;
      const uint32_t tag = (b >> 1) & 1;
      int n = 1;
      float e[8];
      if (unit < 72) {
#pragma unroll 1
        while (true) {
          const bool bad = __any_sync(0xffffffffu, differ4(x[0].x, x[1].x, x[2].x, x[3].x, tag) & 1);
          sum_msg(e, x[0], x[1], x[2], x[3]);
          if (!bad || (left -= 16) <= 0) break;
          ld_msg16x4(x, a.mail + mo);
          n++;
        }
        TS(b, 10);
        TSV(b, 15, n);
        float f[4];
        const bool b4 = lane & 16;
#pragma unroll
        for (int i = 0; i < 4; i++) f[i] = (b4 ? e[4 + i] : e[i]) + __shfl_xor_sync(0xffffffffu, b4 ? e[i] : e[4 + i], 16);
        sts128(sb + OFF_SCR + (lane & 16) * 64 + warp * 256 + (lane & 15) * 16, make_uint4(__float_as_uint(f[0]), __float_as_uint(f[1]), __float_as_uint(f[2]), __float_as_uint(f[3])));
        bar_sync(NB_MR, 128);
        publish(a, b, warp, sb + OFF_SCR + warp * 1024 + (lane & 3) * 64 + (lane >> 2) * 8, (warp & 1) * 10240 + unit * 128 + lane * 4);
      } else if (unit < NUNIT) {
        ld_msg16x2(x + 4, a.mail + (mo ^ mo2));
        __syncwarp();
#pragma unroll 1
        while (true) {
          const bool bad = __any_sync(0xffffffffu, (differ4(x[0].x, x[1].x, x[2].x, x[3].x, tag) | differ4(x[4].x, x[5].x, x[4].x, x[5].x, tag)) & 1);
          sum_msg(e, x[0], x[1], x[2], x[3]);
          e[0] += bf_lo(x[4].x) + bf_lo(x[5].x); e[1] += bf_hi(x[4].x) + bf_hi(x[5].x); e[2] += bf_lo(x[4].y) + bf_lo(x[5].y); e[3] += bf_hi(x[4].y) + bf_hi(x[5].y);
          e[4] += bf_lo(x[4].z) + bf_lo(x[5].z); e[5] += bf_hi(x[4].z) + bf_hi(x[5].z); e[6] += bf_lo(x[4].w) + bf_lo(x[5].w); e[7] += bf_hi(x[4].w) + bf_hi(x[5].w);
          if (!bad || (left -= 16) <= 0) break;
          ld_msg16x6(x, a.mail + mo, a.mail + (mo ^ mo2));
          n++;
        }
        TS(b, 10);
        TSV(b, 15, n);
        float f[4];
        const bool b4 = lane & 16, b3 = lane & 8;
#pragma unroll
        for (int i = 0; i < 4; i++) f[i] = (b4 ? e[4 + i] : e[i]) + __shfl_xor_sync(0xffffffffu, b4 ? e[i] : e[4 + i], 16);
        const float h0 = (b3 ? f[2] : f[0]) + __shfl_xor_sync(0xffffffffu, b3 ? f[0] : f[2], 8);
        const float h1 = (b3 ? f[3] : f[1]) + __shfl_xor_sync(0xffffffffu, b3 ? f[1] : f[3], 8);
        asm volatile("st.shared.v2.f32 [%0],{%1,%2};" ::"r"(sb + OFF_SCR + warp * 256 + lane * 8), "f"(h0), "f"(h1) : "memory");
        bar_sync(NB_MR, 128);
        if (!(warp & 1))
          publish(a, b, warp, sb + OFF_SCR + lane * 8, (lane >> 4) * 10240 + (36 + (unit >> 1)) * 128 + (lane & 3) * 32 + (lane & 8) * 2 + (unit & 1) * 8 + (lane & 4));
      }
      const uint32_t t0 = clk32();
      mo ^= 2048;
      TS(b, 11);
      if (rank < 2) {
        const int q = 2 * rank + (warp >> 1), blk = (warp & 1) ? 4 : q, o = blk * 4096 + ((warp & 1) ? q * 1024 : 0);
        const uint8_t* src = a.mbuf + (uint32_t)((ph ^ 1) * 40960 + o + (blk + ((rsel >> (5 - 5 * ph + blk)) & 1)) * 4096);
        while (clk32() - t0 < B2) {}
        if (elect()) bulk_g2s_mc(sb + OFF_R + o, src, (warp & 1) ? 1024 : 4096, sb + BAR_M + 8 * q);
        __syncwarp();
      }
      TS(b + 1, 12);
    }
  }
  store_o(a, ok, NS - 1, cta, tid0);
  bar_sync(NB_MR, 128);
  if (tid0 == 0) cnt_signal(&g_cnt[CN_O][NS - 1][(cta >> 4) * 32]);
  TS_FLUSH(NS - 1);
  if (left <= 0) g_err = 3;
}

__global__ void __cluster_dims__(3, 1, 1) __launch_bounds__(384, 1)
k_chain(const __grid_constant__ CUtensorMap tmWq, const __grid_constant__ CUtensorMap tmWk, const __grid_constant__ CUtensorMap tmWv,
        const __grid_constant__ CUtensorMap tmWo, const __grid_constant__ CUtensorMap tmX, const __grid_constant__ ChainArgs args) {
  using namespace C;
  extern __shared__ __align__(1024) uint8_t smem[];
  const uint32_t sb = smem_u32(smem);
  const int tid = threadIdx.x;
  const int wg = __shfl_sync(0xffffffffu, tid >> 7, 0);
  const int cta = blockIdx.x, rank = cta % 3;
  DUR(0);
  asm volatile("griddepcontrol.launch_dependents;");
  if (tid == 0) {
    if ((sb & 0xFFFFFF) != SB0) g_err = 100;
    for (int i = 0; i < 3; i++) mbar_init(sb + BAR_F0 + 8 * i, 1);
    mbar_init(sb + BAR_W1, 1); mbar_init(sb + BAR_W2, 1); mbar_init(sb + BAR_W3, 1);
    for (int i = 0; i < 5; i++) mbar_init(sb + BAR_X + 8 * i, 1);
    mbar_init(sb + BAR_OG2, 1);
    mbar_init(sb + BAR_XE, 6); mbar_init(sb + BAR_OG, 1); mbar_init(sb + BAR_OE, 3);
    mbar_init(sb + BAR_ROT, 1); mbar_init(sb + BAR_RQ, 3); mbar_init(sb + BAR_VF, 3); mbar_init(sb + BAR_RF, 3); mbar_init(sb + BAR_RE, 6);
    mbar_init(sb + BAR_RID, 1);
    for (int i = 0; i < 4; i++) mbar_init(sb + BAR_M + 8 * i, 1);
    asm volatile("fence.mbarrier_init.release.cluster;" ::: "memory");
    fence_async();
    mbar_expect_tx(sb + BAR_W1, 163840 + 6 * 8192);
    const int col = (cta / 3) * DH + rank * 64;
    for (int i = 0; i < 10; i++) {
      tma2d(sb + STAGE_Q + i * 8192, &tmWq, col, i * 64, sb + BAR_W1);
      tma2d(sb + STAGE_V + i * 8192, &tmWv, col, i * 64, sb + BAR_W1);
      if (i < 6) tma2d(sb + OFF_WK + i * 8192, &tmWk, col, i * 64, sb + BAR_W1);
    }
  }
  const int unit = rank < 2 ? (cta / 3) * 2 + rank : 64 + cta / 3;
  if ((tid & 31) == 0) {
#pragma unroll 1
    for (int job = 11 - (tid >> 5); job < 18; job += 12) {
      uint32_t best[2] = {SENT, SENT};
      if (job < (unit < 72 ? 14 : unit < NUNIT ? 18 : 10)) {
        uint8_t* p = job < 10 ? args.mbuf + job * 8192 + cta * 32 : args.mail + (size_t)unit * MAIL_UNIT + (job - 10) * 8192;
#pragma unroll 1
        for (int r = 0; r < 12; r++) {
          const uint32_t t0 = clk32();
          uint32_t v;
          asm volatile("atom.relaxed.gpu.global.exch.b32 %0,[%1],%2;" : "=r"(v) : "l"(p + (r & 1) * 4096), "r"(SENT) : "memory");
          uint32_t dt = t0 - 1;
          asm volatile("{.reg .b64 c; .reg .pred p; setp.eq.b32 p,%1,-1; @p mov.u64 c,%%clock64; @p cvt.u32.u64 %0,c;}" : "+r"(dt) : "r"(v) : "memory");
          dt -= t0;
          if (r & 1) best[1] = min(best[1], dt); else best[0] = min(best[0], dt);
        }
      }
      asm volatile("st.shared.u8 [%0],%1;" ::"r"(sb + OFF_SEL + job), "r"((job < 10 ? PL2 : PL1) && best[1] < best[0] ? 1 : 0) : "memory");
    }
  }
  __syncthreads();

  const int tid0 = __shfl_sync(0xffffffffu, tid & 127, tid & 31);
  if (wg == 0) chain_a(tmX, args, sb, tid0, cta, rank, unit);
  else if (wg == 1) chain_q(tmWk, tmWo, tmX, args, sb, tid0, cta, rank);
  else chain_v(args, sb, tid0, cta, rank);
  DUR(2);
  cluster_sync();
}

#define LD 0
#define RLX 0
#define PRE 0
#define HD 0
namespace W {
constexpr int NW = 36, NP = 30, OW0 = 31;
constexpr int QST = 7;
constexpr int OFF_WS = 0;
constexpr int OFF_WQ = 94208;
constexpr int OFF_G = 176128;
constexpr int OFF_GO = 8192;
constexpr int OFF_Q = OFF_G + 24576;
constexpr int PITCH = 144;
constexpr int OFF_STG = OFF_Q;
constexpr int OFF_HIST = OFF_Q + QST * 4096;
constexpr int OFF_ST = OFF_HIST + 2240;
constexpr int OFF_BAR = OFF_ST + 256;
constexpr int SMEM = OFF_BAR + 272;
constexpr int BAR_GF = OFF_BAR, BAR_GE = OFF_BAR + 64, BAR_QF = OFF_BAR + 128, BAR_QE = OFF_BAR + 184, BAR_W1 = OFF_BAR + 240, BAR_W2 = OFF_BAR + 248,
              BAR_H = OFF_BAR + 256;
constexpr int NB_PRO = 1, NB_Q = 2, NB_L = 3, NB_L2 = 4, NB_A = 5;
constexpr uint32_t sb = C::SB0;
static_assert(SMEM <= 232448, "shared memory");
template <bool IS_O> __host__ __device__ constexpr bool in_smem(int k) { return IS_O ? k == 39 : (k & 7) == 2 || (k & 7) == 4 || ((k & 7) == 7 && k != 63); }
template <bool IS_O> __host__ __device__ constexpr int smem_before(int k) { return IS_O ? 0 : 3 * (k >> 3) + ((k & 7) > 2) + ((k & 7) > 4); }
template <bool IS_O> __host__ __device__ constexpr int chunk_k(int c) { return IS_O ? 5 * c : c < 4 ? 6 * c : 4 + 5 * c; }
template <bool IS_O> __host__ __device__ constexpr int stage_off(int c) { return IS_O ? OFF_GO + c * 5120 : OFF_G + (c & 3) * 6144; }
}

struct WorkArgs {
  const bf16* x0;
  bf16* out;
  const bf16* wqkv;
  uint64_t pd[24], od[40], qd[14], qw[42];
};
static void fill_descs(WorkArgs& a) {
  using namespace W;
  for (int k = 0; k < 24; k++) a.pd[k] = mkdesc64(sb + OFF_G + k * 1024, 512, 512);
  for (int k = 0; k < 40; k++) a.qw[k] = mkdesc(sb + OFF_WQ + k * 2048, 8192, 1024);
  for (int k = 0; k < 40; k++) a.od[k] = mkdesc_ns(sb + OFF_GO + k * 1024, 512, 128);
  for (int k = 0; k < 14; k++) a.qd[k] = mkdesc64(sb + OFF_Q + (k >> 1) * 4096 + (k & 1) * 32, 16, 512);
}
__device__ __forceinline__ void cnt_wait_warp(const uint32_t* p, uint32_t target, int& left) {
  while (__any_sync(0xffffffffu, ld_acquire(p) < target) && (left -= 16) > 0) {}
}
__device__ __forceinline__ void pass_wait(uint32_t target, int& left) {
  uint32_t v;
  do {
    asm volatile("ld.acquire.cta.shared.u32 %0,[%1];" : "=r"(v) : "r"(W::sb + W::BAR_H) : "memory");
    if (!__any_sync(0xffffffffu, v < target)) break;
    __nanosleep(30);
  } while (--left > 0);
}
__device__ __forceinline__ const uint8_t* opaque(const uint8_t* p) {
  return reinterpret_cast<const uint8_t*>(__shfl_sync(0xffffffffu, reinterpret_cast<unsigned long long>(p), 0));
}
__device__ __forceinline__ uint4 ld_relaxed16(const void* p) {
  uint4 v; asm volatile("ld.relaxed.gpu.global.v4.u32 {%0,%1,%2,%3},[%4];" : "=r"(v.x), "=r"(v.y), "=r"(v.z), "=r"(v.w) : "l"(p) : "memory"); return v;
}
__device__ __forceinline__ uint4 ld_msg8x2(const void* p) {
  uint4 v;
  asm volatile("{.reg .b64 a,b; ld.relaxed.gpu.global.v2.b64 {a,b},[%4]; mov.b64 {%0,%1},a; mov.b64 {%2,%3},b;}" : "=r"(v.x), "=r"(v.y), "=r"(v.z), "=r"(v.w) : "l"(p) : "memory");
  return v;
}
__device__ __forceinline__ void st_msg8(void* p, uint32_t x, uint32_t y) {
  asm volatile("{.reg .b64 r; mov.b64 r,{%1,%2}; st.relaxed.gpu.global.b64 [%0],r;}" ::"l"(p), "r"(x), "r"(y) : "memory");
}
template <bool LATE>
__device__ __forceinline__ bool job_of(int n, int& l, int& s) {
  const int i = n >> 1, j = n & 1;
  l = j; s = i - j * (LAG + LATE);
  return s >= 0 && s < NSEG;
}

template <bool IS_O>
__device__ __forceinline__ void work_g_weights(const CUtensorMap& tm, int w, int warp, bool second) {
  using namespace W;
  constexpr int NK = IS_O ? 40 : 64;
  const int col = (IS_O ? w - OW0 : w % 5) * 128, row = IS_O ? 0 : (w / 5) * 1024;
  int ns = 0;
#pragma unroll 1
  for (int k = 0; k < NK; k++) {
    const bool s = in_smem<IS_O>(k);
    if (s == second && (k & 1) == (warp & 1)) {
      const int t = warp >> 1;
      tma2d(sb + (s ? OFF_WS + (t * (IS_O ? 1 : 23) + ns) * 2048 : (t * 41 + k - ns) * 2048), &tm, col + t * 64, row + k * 16, sb + (s ? BAR_W2 : BAR_W1));
    }
    ns += s;
  }
}

template <bool IS_O>
__device__ __forceinline__ void work_g_producer(int w) {
  using namespace W;
  constexpr int NC = IS_O ? 8 : 12;
  int left = SPIN_BUDGET;
  uint32_t ph = 1;
#pragma unroll 1
  for (int i = 0; i < NS + IS_O; i++) {
    if (NOX && !IS_O && i >= LAG - 1 && i - LAG + 1 < NSEG) cnt_wait_warp(&g_cnt[CN_X][i - LAG + 1][0], 4, left);
    if (!IS_O) {
      cnt_wait_warp(&g_cnt[CN_O][i][(w / 5) * 32], 16, left);
      if (w == WW) WTS(i, 0);
      fence_async_all();
    }
#pragma unroll 1
    for (int j = 0; j < 2; j++) {
      int l, s;
      if (!job_of<IS_O>(2 * i + j, l, s)) continue;
      if (IS_O) {
        cnt_wait_warp(&g_cnt[CN_A][s][l * 32], 32, left);
        if (w == 35 && (l == 0 || i >= NSEG)) WTS(i, 8);
        fence_async_all();
      }
      const uint8_t* src = opaque(IS_O ? g_ob[s & 7][l] : g_o[i & 7][l][(w / 5) * 16]);
#pragma unroll 1
      for (int r = 0; r < NC / 4; r++) {
        const int n = !IS_O && r == 0 ? 6144 : 5120, s0 = IS_O ? 4 * r : 0;
#pragma unroll
        for (int c = 0; c < 4; c++) {
          mbar_wait(sb + BAR_GE + 8 * (s0 + c), ph, left);
          if (elect()) {
            mbar_expect_tx(sb + BAR_GF + 8 * (s0 + c), n);
            bulk_g2s(sb + stage_off<IS_O>(c) + s0 * 5120, src, n, sb + BAR_GF + 8 * (s0 + c));
          }
          src += n;
        }
        if (!IS_O || r) ph ^= 1;
      }
    }
  }
}

__device__ __forceinline__ uint32_t add_bf2(uint32_t a, uint32_t b) { uint32_t r; asm("add.rn.bf16x2 %0,%1,%2;" : "=r"(r) : "r"(a), "r"(b)); return r; }
template <int N, int LOW>
__device__ __forceinline__ void merge_stats(float m0, float m1, float q0, float q1, float& m, float& q, int lane) {
  const bool up = lane & 16;
  m = up ? m1 : m0; q = up ? q1 : q0;
  float n = 0.5f * N;
#pragma unroll
  for (int o = 16; o >= LOW; o >>= 1) {
    const float mo = __shfl_xor_sync(0xffffffffu, o < 16 ? m : up ? m0 : m1, o), qo = __shfl_xor_sync(0xffffffffu, o < 16 ? q : up ? q0 : q1, o);
    const float d = mo - m;
    m = fmaf(0.5f, d, m); q = fmaf(n * d, d, q + qo);
    n *= 2.f;
  }
}
template <int LOW>
__device__ __forceinline__ void pair_stats(const uint32_t (&x)[20], float& m, float& q, int lane) {
  float m0 = 0.f, m1 = 0.f, q0 = 0.f, q1 = 0.f;
#pragma unroll
  for (int j = 0; j < 20; j++) {
    const float e = bf_lo(x[j]), f = bf_hi(x[j]);
    m0 += e; m1 += f; q0 = fmaf(e, e, q0); q1 = fmaf(f, f, q1);
  }
  merge_stats<20, LOW>(m0 * 0.05f, m1 * 0.05f, fmaxf(fmaf(m0 * -0.05f, m0, q0), 0.f), fmaxf(fmaf(m1 * -0.05f, m1, q1), 0.f), m, q, lane);
}
__device__ __forceinline__ void add_product(uint32_t (&r)[20], const uint4 (&x)[5]) {
#pragma unroll
  for (int n = 0; n < 20; n++) {
    const uint4& v = x[n >> 2];
    const float2 f = unpack_h2((n & 3) == 0 ? v.x : (n & 3) == 1 ? v.y : (n & 3) == 2 ? v.z : v.w);
    r[n] = add_bf2(r[n], pack_bf16(f.x, f.y));
  }
}
__device__ __forceinline__ void load20(uint32_t (&r)[20], const uint8_t* p, int stride) {
#pragma unroll
  for (int m = 0; m < 5; m++) { const uint4 u = ld_relaxed16(p + m * stride); r[4 * m] = u.x; r[4 * m + 1] = u.y; r[4 * m + 2] = u.z; r[4 * m + 3] = u.w; }
}
__device__ __forceinline__ void poll5(uint4 (&x)[5], const uint8_t* src, int stride, uint32_t tag, int& left) {
#pragma unroll 1
  while (true) {
#pragma unroll
    for (int j = 0; j < 5; j++) x[j] = ld_msg8x2(src + j * stride);
    __syncwarp();
    const uint32_t bad = differ4(x[0].x, x[0].z, x[1].x, x[1].z, tag) | differ4(x[2].x, x[2].z, x[3].x, x[3].z, tag) | differ4(x[4].x, x[4].z, x[4].x, x[4].z, tag);
    if (!__any_sync(0xffffffffu, bad & 1) || (left -= 16) <= 0) break;
  }
}
__device__ __forceinline__ uint32_t norm_lo(uint32_t a, uint32_t b, float q, float m) { return pack_bf16(fmaf(bf_lo(a), q, m), fmaf(bf_lo(b), q, m)); }
__device__ __forceinline__ uint32_t norm_hi(uint32_t a, uint32_t b, float q, float m) { return pack_bf16(fmaf(bf_hi(a), q, m), fmaf(bf_hi(b), q, m)); }
__device__ __forceinline__ float part_var(float mp, float q, float n, float m) { const float d = mp - m; return fmaf(n * d, d, q); }
#define F(x) __uint_as_float(x)

__device__ __forceinline__ void work_l(const WorkArgs& a, int lane0, int p, int mask) {
  using namespace W;
  int left = SPIN_BUDGET;
#pragma unroll 1
  for (int n = 0; n < 2 * NS; n++) {
    int l, s;
    if (!job_of<false>(n, l, s) || !((mask >> l) & 1)) continue;
    cnt_wait_warp(&g_cnt[CN_P][s][l * 32], NP, left);
    if (p == 5 && lane0 == 0 && (l == 0 || n >= 2 * NSEG - 1)) WTS((n + 1) >> 1, 14);
    int lane = fresh(lane0);
    uint32_t r[20];
    const uint32_t ao = (p & 3) * 10240 + (p >> 2) * 64 + (lane >> 2) * 256 + (lane & 3) * 16;
    {
      uint4 x[5];
      const uint8_t* acc = g_part[s % MD][l] + ao;
#pragma unroll
      for (int m = 0; m < 5; m++) x[m] = ld_relaxed16(acc + m * 2048);
      if (l) {
        load20(r, g_xs[1] + (uint32_t)((s * 4 + (p >> 2)) * 10240 + (p & 3) * 16 + lane * 64), 2048);
      } else {
        const uint2* q = reinterpret_cast<const uint2*>(a.x0) + (uint32_t)((s * 16 + p) * 320 + lane);
#pragma unroll
        for (int m = 0; m < 5; m++)
          asm volatile("ld.global.nc.v2.u32 {%0,%2},[%4]; ld.global.nc.v2.u32 {%1,%3},[%4+1280];"
                       : "=r"(r[4 * m]), "=r"(r[4 * m + 1]), "=r"(r[4 * m + 2]), "=r"(r[4 * m + 3]) : "l"(q + m * 32));
        __syncwarp();
#pragma unroll
        for (int j = 0; j < 20; j += 2) { const uint32_t u = r[j]; r[j] = __byte_perm(u, r[j + 1], 0x5410); r[j + 1] = __byte_perm(u, r[j + 1], 0x7632); }
      }
      __syncwarp();
      add_product(r, x);
    }
    __syncwarp();
    lane = fresh(lane0);
    uint8_t* acc = g_part[s % MD][l] + ao;
    uint8_t* xp = g_xs[2 * l] + (uint32_t)((s * 16 + p) * 2560 + lane * 16);
#pragma unroll
    for (int m = 0; m < 5; m++) {
      *reinterpret_cast<uint4*>(xp + m * 512) = make_uint4(r[4 * m], r[4 * m + 1], r[4 * m + 2], r[4 * m + 3]);
      *reinterpret_cast<uint4*>(acc + m * 2048) = make_uint4(0, 0, 0, 0);
    }
    float m, q;
    pair_stats<1>(r, m, q, lane);
    q = rsqrtf(q * (1.f / DM) + 1e-5f);
    m *= -q;
    const float q0 = __shfl_sync(0xffffffffu, q, 0), q1 = __shfl_sync(0xffffffffu, q, 16);
    const float m0 = __shfl_sync(0xffffffffu, m, 0), m1 = __shfl_sync(0xffffffffu, m, 16);
    uint8_t* img = g_xnb[((n + 1) >> 1) & 7] + (uint32_t)((lane >> 3) * 4096 + (l * 16 + p) * 128 + (((lane & 7) ^ ((p & 3) << 1)) << 3));
#pragma unroll
    for (int j = 0; j < 20; j += 4) {
      __syncwarp();
      *reinterpret_cast<uint2*>(img + j * 4096) = make_uint2(norm_lo(r[j], r[j + 1], q0, m0), norm_lo(r[j + 2], r[j + 3], q0, m0));
      *reinterpret_cast<uint2*>(img + j * 4096 + 64) = make_uint2(norm_hi(r[j], r[j + 1], q1, m1), norm_hi(r[j + 2], r[j + 3], q1, m1));
    }
    __syncwarp();
    if (p == 5 && lane == 0 && (l == 0 || n >= 2 * NSEG - 1)) WTS((n + 1) >> 1, 4);
    if (elect()) cnt_signal(&g_cnt[CN_L][(n + 1) >> 1][0]);
    __syncwarp();
  }
  if (left <= 0) g_err = 14;
}

template <bool IS_O>
__device__ __forceinline__ void work_g(const WorkArgs& a, int w, int tile, int tid0) {
  using namespace W;
  constexpr int NC = IS_O ? 8 : 12, NST = IS_O ? 8 : 4;
  int left = SPIN_BUDGET;
  uint32_t ph = 0;
  constexpr int NR = IS_O ? 39 : 41;
  uint32_t wf[NR][4];
  mbar_wait(sb + BAR_W1, 0, left);
  load_wfrags<NR>(wf, sb + tile * 41 * 2048, tid0 >> 5, tid0 & 31);
  bar_sync(NB_PRO, 512);
  mbar_wait(sb + BAR_W2, 0, left);
  cnt_wait_warp(&g_cnt[CN_Z][0][0], NW, left);
  const uint32_t wlo = (uint32_t)mkdesc(C::SB0 + OFF_WS, 8192, 1024) + tile * (IS_O ? 128 : 23 * 128);
  constexpr uint32_t WHI = (uint32_t)(mkdesc(0, 8192, 1024) >> 32);
  const int g = (tid0 & 31) >> 2, t = tid0 & 3;
  const int col = (IS_O ? w - OW0 : w % 5) * 128 + tile * 64 + (tid0 >> 5) * 16 + ((g & 1) ? g + 7 : g);
  const uint32_t mo = (col >> 4) * 256 + t * 64 + (col & 15) * 4, mo0 = IS_O ? (col >> 2) * 64 + t * 16 + (col & 3) * 4 : mo;
#pragma unroll 1
  for (int il = 0; il < 2 * (NS + 1); il++) {
    int l, s;
    if (!job_of<IS_O>(il, l, s)) continue;
    float d[16];
    bool ok = false;
#pragma unroll
    for (int c = 0; c < NC; c++) {
      if (!PRE || !ok) mbar_wait(sb + BAR_GF + 8 * (c % NST), ph ^ ((c / NST) & 1), left);
      if (PRE && c + 1 < NC) ok = mbar_test(sb + BAR_GF + 8 * ((c + 1) % NST), ph ^ (((c + 1) / NST) & 1));
      if (c == 0 && w == (IS_O ? 35 : WW) && tid0 == 0 && tile == 0 && l == 0) WTS(il >> 1, IS_O ? 9 : 1);
      wg_fence();
#pragma unroll
      for (int k = chunk_k<IS_O>(c); k < chunk_k<IS_O>(c + 1); k++) {
        const uint64_t db = IS_O ? a.od[k] : a.pd[(c & 3) * 6 + k - chunk_k<IS_O>(c)];
        if (in_smem<IS_O>(k)) {
          const uint64_t da = desc2(wlo + smem_before<IS_O>(k) * 128, WHI);
          if (IS_O) wgmma_ts32(d, da, db, 1); else wgmma_tt32(d, da, db, 1);
        } else {
          if (IS_O) wgmma_rs32(d, wf[k - smem_before<IS_O>(k)], db, k); else wgmma_rt32(d, wf[k - smem_before<IS_O>(k)], db, k);
        }
      }
      wg_commit();
      if (c > 0) {
        wg_wait<1>();
        if (tid0 == 0) mbar_arrive(sb + BAR_GE + 8 * ((c - 1) % NST));
      }
    }
    ph ^= 1;
    wg_wait<0>();
    if (tid0 == 0) mbar_arrive(sb + BAR_GE + 8 * (NST - 1));
    uint8_t* dst = (IS_O ? g_prod[s % MD][l] : g_part[s % MD][l]) + (l ? mo : mo0);
    const uint32_t tag = (s / MD) & 1;
#pragma unroll
    for (int j = 0; j < 4; j++) {
      const uint32_t w0 = pack_h2(d[4 * j], d[4 * j + 1]), w1 = pack_h2(d[4 * j + 2], d[4 * j + 3]);
      const uint32_t r = __shfl_xor_sync(0xffffffffu, (g & 1) ? w0 : w1, 4);
      if (IS_O) st_msg8(dst + j * 10240, (((g & 1) ? r : w0) & ~1u) | tag, (g & 1) ? w1 : r);
      else asm volatile("red.relaxed.gpu.global.add.noftz.v2.f16x2 [%0],{%1,%2};" ::"l"(dst + j * 10240), "r"((g & 1) ? r : w0), "r"((g & 1) ? w1 : r) : "memory");
    }
    __syncwarp();
    if ((tid0 & 31) == 0) asm volatile("red.release.cta.shared.add.u32 [%0],1;" ::"r"(sb + BAR_H) : "memory");
    if (w == (IS_O ? 35 : WW) && tid0 == 0 && tile == 0) WTS(il >> 1, (IS_O ? 10 : 2) + l);
  }
  if (left <= 0) g_err = 11;
}

__device__ __forceinline__ void work_q_producer() {
  using namespace W;
  int left = SPIN_BUDGET;
#pragma unroll 1
  for (int i = 0; i <= NS; i++) {
    const uint8_t* src = opaque(g_xnb[i & 7]);
    cnt_wait_warp(&g_cnt[CN_L][i][0], (i < NSEG ? 16 : 0) + (i > LAG ? 16 : 0), left);
    if ((int)blockIdx.x == WW) WTS(i, 5);
    fence_async_all();
#pragma unroll 1
    for (int r = 0; r < 3; r++, src += QST * 4096) {
#pragma unroll
      for (int c = 0; c < QST; c++) {
        if (c == QST - 1 && r == 2) break;
        mbar_wait(sb + BAR_QE + 8 * c, ((c < QST - 1 ? i + r : r) & 1) ^ 1, left);
        if (elect()) {
          mbar_expect_tx(sb + BAR_QF + 8 * c, 4096);
          bulk_g2s(sb + OFF_Q + c * 4096, src + c * 4096, 4096, sb + BAR_QF + 8 * c);
        }
      }
    }
  }
}

__device__ __forceinline__ void work_q(const WorkArgs& a, int w, int tid0) {
  using namespace W;
  int left = SPIN_BUDGET;
  const int warp = __shfl_sync(0xffffffffu, tid0 >> 5, 0);
#pragma unroll 1
  for (int i = 0; i <= NS; i++) {
    {
      if (warp == 3 && i + 6 < NSEG && (tid0 & 31) < 20) {
        const int j = tid0 & 31;
        prefetch_l2((j < 10 ? g_xn[0] : reinterpret_cast<const uint8_t*>(a.x0)) + (size_t)(i + 6) * 40960 + (w * 10 + j % 10) * 128);
      }
      __syncwarp();
    }
    {
      float d[32] = {};
#pragma unroll 1
      for (int r = 0; r < 3; r++) {
#pragma unroll
        for (int c = 0; c < QST; c++) {
          if (c == QST - 1 && r == 2) break;
          mbar_wait(sb + BAR_QF + 8 * c, (c < QST - 1 ? i + r : r) & 1, left);
          wg_fence();
#pragma unroll
          for (int k = 2 * c; k < 2 * c + 2; k++) wgmma_ts64(d, a.qw[14 * r + k], a.qd[k], 1);
          wg_commit();
          wg_wait<1>();
          if ((c ? r < 2 : r > 0) && tid0 == 0) mbar_arrive(sb + BAR_QE + 8 * ((c + QST - 1) % QST));
        }
      }
      wg_wait<0>();
      if (w == WW && tid0 == 0) WTS(i, 6);
      const int lane = fresh(tid0) & 31;
      const uint32_t o = sb + OFF_STG + ((lane >> 4) * 8 + (lane & 7)) * PITCH + warp * 32 + (lane & 8) * 2;
      bar_sync(NB_Q, 128);
#pragma unroll
      for (int j = 0; j < 4; j++)
        stsm4t(o + 16 * j * PITCH, pack_bf16(d[8 * j], d[8 * j + 1]), pack_bf16(d[8 * j + 2], d[8 * j + 3]), pack_bf16(d[8 * j + 4], d[8 * j + 5]),
               pack_bf16(d[8 * j + 6], d[8 * j + 7]));
      bar_sync(NB_Q, 128);
    }
#pragma unroll 1
    for (int j = 0; j < 2; j++) {
      int l, s;
      if (!job_of<true>(2 * i + j, l, s)) continue;
      const bool ts = w == WW && (l == 0 || i >= NSEG);
      {
        const int tid = fresh(tid0), tk = tid >> 2, h = tid & 3;
        const float scl = 0.22360679774997896f * 1.4426950408889634f;
        const uint32_t kn = sb + OFF_STG + (l * 32 + tk) * PITCH + 40, ko = sb + OFF_HIST + (l * 14 + 14 + tk) * 80;
        float sc[2];
        {
          float q[20];
#pragma unroll
          for (int j = 0; j < 5; j++) {
            const uint2 u = lds64(kn - 40 + j * 8);
            q[4 * j] = bf_lo(u.x); q[4 * j + 1] = bf_hi(u.x); q[4 * j + 2] = bf_lo(u.y); q[4 * j + 3] = bf_hi(u.y);
          }
#pragma unroll
          for (int e = 0; e < 2; e++) {
            const int d = 4 * h + 2 * e;
            const uint32_t kv = tk >= d ? kn - d * PITCH : ko - d * 80;
            float s0 = 0.f, s1 = 0.f;
#pragma unroll
            for (int n = 0; n < 5; n++) {
              const uint2 u = lds64(kv + n * 8);
              s0 = fmaf(q[4 * n], bf_lo(u.x), s0); s1 = fmaf(q[4 * n + 1], bf_hi(u.x), s1);
              s0 = fmaf(q[4 * n + 2], bf_lo(u.y), s0); s1 = fmaf(q[4 * n + 3], bf_hi(u.y), s1);
            }
            sc[e] = s * 32 + tk >= d ? (s0 + s1) * scl : -INFINITY;
          }
        }
        uint32_t v[8][3];
#pragma unroll
        for (int j = 0; j < 8; j++) {
          const uint32_t kv = (tk >= 2 * j ? kn - 2 * j * PITCH : ko - 2 * j * 80) + 40 + h * 4;
          v[j][0] = lds32(kv); v[j][1] = lds32(kv + 16); v[j][2] = lds32(kv + (h < 2 ? 32 : 0));
        }
        float mx = fmaxf(sc[0], sc[1]);
        mx = fmaxf(fmaxf(mx, __shfl_xor_sync(0xffffffffu, mx, 1)), fmaxf(__shfl_xor_sync(0xffffffffu, mx, 2), __shfl_xor_sync(0xffffffffu, mx, 3)));
        sc[0] = ex2(sc[0] - mx); sc[1] = ex2(sc[1] - mx);
        const float inv = rcp(quad_sum(sc[0] + sc[1]));
        const uint32_t pp = pack_bf16(sc[0] * inv, sc[1] * inv);
        float o[6] = {};
#pragma unroll
        for (int j = 0; j < 4; j++) {
          const uint32_t p = __shfl_sync(0xffffffffu, pp, j, 4);
#pragma unroll
          for (int n = 0; n < 3; n++) {
            o[2 * n] = fmaf(bf_lo(p), bf_lo(v[2 * j][n]), o[2 * n]); o[2 * n + 1] = fmaf(bf_lo(p), bf_hi(v[2 * j][n]), o[2 * n + 1]);
            o[2 * n] = fmaf(bf_hi(p), bf_lo(v[2 * j + 1][n]), o[2 * n]); o[2 * n + 1] = fmaf(bf_hi(p), bf_hi(v[2 * j + 1][n]), o[2 * n + 1]);
          }
        }
        const int c = w * 10 + h;
        uint8_t* img = g_ob[s & 7][l] + tk * 16 + (c >> 2) * 512 + (c & 3) * 4;
#pragma unroll
        for (int n = 0; n < 3; n++)
          if (n < 2 || h < 2) *reinterpret_cast<uint32_t*>(img + n * 512) = pack_bf16(o[2 * n], o[2 * n + 1]);
      }
      bar_sync(NB_A, 160);
      if (ts && tid0 == 0) WTS(i, 15);
      {
        const int tid = fresh(tid0), r = tid >> 3, c = tid & 7;
        if (r < 14 && c < 5) {
          const uint32_t p = sb + OFF_STG + (l * 32 + 18 + r) * PITCH + 40 + c * 16;
          const uint2 u = lds64(p), v = lds64(p + 8);
          sts128(sb + OFF_HIST + (l * 14 + r) * 80 + c * 16, make_uint4(u.x, u.y, v.x, v.y));
        }
        __syncwarp();
      }
    }
    fence_async();
    bar_sync(NB_Q, 128);
    if (tid0 < QST - 1) mbar_arrive(sb + BAR_QE + 8 * tid0);
    __syncwarp();
  }
  if (left <= 0) g_err = 12;
}

__device__ __forceinline__ void work_f(const WorkArgs& a, int w, int tid0) {
  using namespace W;
  int left = SPIN_BUDGET;
  uint32_t passes = 0;
  const int warp = __shfl_sync(0xffffffffu, tid0 >> 5, 0), grp = w - 32;
#pragma unroll 1
  for (int n = 0; n < 2 * (NS + 1); n++) {
    int l, s;
    if (!job_of<true>(n, l, s)) continue;
    const int lane = fresh(tid0) & 31;
    cnt_wait_warp(&g_cnt[CN_A][s][l * 32], 32, left);
    uint32_t r[20];
    uint4 x[5];
    const uint8_t* res = g_xs[2 * l] + (uint32_t)(s * 40960 + grp * 10240);
    const uint8_t* src = g_prod[s % MD][l] + grp * 10240;
    if (l) load20(r, res + (warp * 2560 + lane * 16), 512);
    else load20(r, res + ((lane & 3) * 2560 + warp * 640 + (lane >> 2) * 16), 128);
    pass_wait(passes += 8, left);
    if (HD) { const uint32_t t0 = clk32(); while (clk32() - t0 < HD) {} }
    if (l) poll5(x, src + (warp * 64 + (lane >> 2) * 256 + (lane & 3) * 16), 2048, (s / MD) & 1, left);
    else poll5(x, src + (warp * 2560 + lane * 16), 512, (s / MD) & 1, left);
    add_product(r, x);
    if (l == 0) {
      uint8_t* xp = g_xs[1] + (uint32_t)(s * 40960 + grp * 10240 + warp * 2560 + lane * 16);
#pragma unroll
      for (int j = 0; j < 5; j++) *reinterpret_cast<uint4*>(xp + j * 512) = make_uint4(r[4 * j], r[4 * j + 1], r[4 * j + 2], r[4 * j + 3]);
      float m, q;
      pair_stats<4>(r, m, q, lane);
      if (!(lane & 12)) asm volatile("st.shared.v2.f32 [%0],{%1,%2};" ::"r"(sb + OFF_ST + (lane & 3) * 64 + (lane & 16) * 2 + warp * 8), "f"(m), "f"(q) : "memory");
      const bool odd = lane & 4;
      const uint32_t keep = odd ? 0x7632 : 0x5410, give = odd ? 0x5410 : 0x7632;
#pragma unroll
      for (int j = 0; j < 20; j += 4) {
        const uint32_t k0 = __byte_perm(r[j], r[j + 1], keep), k1 = __byte_perm(r[j + 2], r[j + 3], keep);
        const uint32_t g0 = __shfl_xor_sync(0xffffffffu, __byte_perm(r[j], r[j + 1], give), 4), g1 = __shfl_xor_sync(0xffffffffu, __byte_perm(r[j + 2], r[j + 3], give), 4);
        r[j] = odd ? g0 : k0; r[j + 1] = odd ? g1 : k1; r[j + 2] = odd ? k0 : g0; r[j + 3] = odd ? k1 : g1;
      }
      bar_sync(NB_Q, 128);
      const uint32_t sa = sb + OFF_ST + (lane & 3) * 64 + (lane & 4) * 8;
      const uint4 e0 = lds128(sa), e1 = lds128(sa + 16);
      m = 0.25f * ((F(e0.x) + F(e0.z)) + (F(e1.x) + F(e1.z)));
      q = rsqrtf(((part_var(F(e0.x), F(e0.y), 160.f, m) + part_var(F(e0.z), F(e0.w), 160.f, m)) +
                  (part_var(F(e1.x), F(e1.y), 160.f, m) + part_var(F(e1.z), F(e1.w), 160.f, m))) * (1.f / DM) + 1e-5f);
      m *= -q;
      uint8_t* dst = g_xn[1] + (uint32_t)((s * 4 + grp) * 10240 + (warp * 20 + (lane >> 3)) * 128 + (lane & 3) * 32 + (lane & 4) * 4);
#define NRM(V) pack_bf16(fmaf(bf_lo(V), q, m), fmaf(bf_hi(V), q, m))
#pragma unroll
      for (int j = 0; j < 20; j += 4) *reinterpret_cast<uint4*>(dst + j * 128) = make_uint4(NRM(r[j]), NRM(r[j + 1]), NRM(r[j + 2]), NRM(r[j + 3]));
#undef NRM
      bar_sync(NB_Q, 128);
      if (warp == 0 && elect()) cnt_signal(&g_cnt[CN_X][s][0]);
      __syncwarp();
    } else {
      uint2* dst = reinterpret_cast<uint2*>(a.out) + (uint32_t)((s * 16 + grp * 4 + warp) * 320 + lane);
#pragma unroll
      for (int j = 0; j < 20; j += 4) {
        dst[j * 8] = make_uint2(__byte_perm(r[j], r[j + 1], 0x5410), __byte_perm(r[j + 2], r[j + 3], 0x5410));
        dst[160 + j * 8] = make_uint2(__byte_perm(r[j], r[j + 1], 0x7632), __byte_perm(r[j + 2], r[j + 3], 0x7632));
      }
    }
    if (w == 35 && tid0 == 0) WTS(n >> 1, 12 + l);
  }
  if (left <= 0) g_err = 13;
}
#undef F

__global__ void __launch_bounds__(512, 1)
k_work(const __grid_constant__ CUtensorMap tmWo, const __grid_constant__ CUtensorMap tmBo, const __grid_constant__ WorkArgs args) {
  using namespace W;
  extern __shared__ __align__(1024) uint8_t smem[];
  const int tid = threadIdx.x, w = blockIdx.x;
  const int wg = __shfl_sync(0xffffffffu, tid >> 7, 0);
  const int tid0 = __shfl_sync(0xffffffffu, tid & 127, tid & 31);
  if (tid == 0) {
    if (smem_u32(smem) != sb) g_err = 101;
    for (int i = 0; i < 8; i++) { mbar_init(sb + BAR_GF + 8 * i, 1); mbar_init(sb + BAR_GE + 8 * i, 2); }
    for (int i = 0; i < QST; i++) { mbar_init(sb + BAR_QF + 8 * i, 1); mbar_init(sb + BAR_QE + 8 * i, 1); }
    mbar_init(sb + BAR_W1, 1); mbar_init(sb + BAR_W2, 1); sts32(sb + BAR_H, 0); sts32(sb + BAR_H + 4, 0);
    asm volatile("fence.mbarrier_init.release.cluster;" ::: "memory");
    fence_async();
    mbar_expect_tx(sb + BAR_W1, (w < NP ? 82 : 78) * 2048);
    mbar_expect_tx(sb + BAR_W2, (w < NP ? 46 : 2) * 2048);
  }
  __syncthreads();

  if (wg < 2 && w < NP) {
    asm volatile("setmaxnreg.inc.sync.aligned.u32 208;");
    work_g<false>(args, w, wg, tid0);
  } else if (wg < 2) {
    asm volatile("setmaxnreg.inc.sync.aligned.u32 200;");
    if (w >= OW0) work_g<true>(args, w, wg, tid0);
    else {
      bar_sync(NB_PRO, 512);
      work_l(args, tid0 & 31, 12 + __shfl_sync(0xffffffffu, tid0 >> 5, 0), 1 << wg);
    }
  } else if (wg == 2 && w < 32) {
    asm volatile("setmaxnreg.dec.sync.aligned.u32 72;");
    for (int i = tid0; i < MD * 160; i += 128) reinterpret_cast<uint4*>(g_part[i / 160][w >> 4] + (w & 15) * 2560)[i % 160] = make_uint4(0, 0, 0, 0);
    bar_sync(NB_Q, 128);
    if (tid0 == 0) cnt_signal(&g_cnt[CN_Z][0][0]);
    for (int i = tid0; i < 560; i += 128) sts32(sb + OFF_HIST + i * 4, 0);
    bar_sync(NB_PRO, 512);
#pragma unroll 16
    for (int i = tid0; i < 640 * 32; i += 128) {
      const int k = i >> 5, c = i & 31;
      uint32_t v = 0;
      if (c < 30) v = *reinterpret_cast<const uint32_t*>(args.wqkv + (size_t)k * 1920 + (c / 10) * 640 + w * 20 + (c % 10) * 2);
      sts32(sb + OFF_WQ + (k >> 6) * 8192 + (k & 63) * 128 + (((c >> 2) ^ (k & 7)) << 4) + (c & 3) * 4, v);
    }
    fence_async();
    bar_sync(NB_Q, 128);
    work_q(args, w, tid0);
  } else if (wg == 2) {
    asm volatile("setmaxnreg.dec.sync.aligned.u32 56;");
    for (int i = tid0; i < MD * 1280; i += 128) reinterpret_cast<uint4*>(g_prod[i / 1280][(i / 640) & 1] + (w - 32) * (4 * 2560))[i % 640] = make_uint4(SENT, SENT, SENT, SENT);
    bar_sync(NB_Q, 128);
    if (tid0 == 0) cnt_signal(&g_cnt[CN_Z][0][0]);
    bar_sync(NB_PRO, 512);
    work_f(args, w, tid0);
  } else if (w >= 32) {
    asm volatile("setmaxnreg.dec.sync.aligned.u32 56;");
    const int warp = __shfl_sync(0xffffffffu, tid0 >> 5, 0);
    if (elect()) work_g_weights<true>(tmBo, w, warp, false);
    __syncwarp();
    bar_sync(NB_PRO, 512);
    if (elect()) work_g_weights<true>(tmBo, w, warp, true);
    __syncwarp();
    if (warp == 0) work_g_producer<true>(w);
    else work_l(args, tid0 & 31, (w - 32) * 3 + warp - 1, 3);
  } else {
    asm volatile("setmaxnreg.dec.sync.aligned.u32 24;");
    const int warp = __shfl_sync(0xffffffffu, tid0 >> 5, 0);
    if (elect()) {
      if (w < NP) work_g_weights<false>(tmWo, w, warp, false);
      else if (w >= OW0) work_g_weights<true>(tmBo, w, warp, false);
    }
    __syncwarp();
    bar_sync(NB_PRO, 512);
    if (elect()) {
      if (w < NP) work_g_weights<false>(tmWo, w, warp, true);
      else if (w >= OW0) work_g_weights<true>(tmBo, w, warp, true);
    }
    __syncwarp();
    if (warp == 0) {
      if (w < NP) work_g_producer<false>(w);
      else if (w >= OW0) work_g_producer<true>(w);
    } else if (warp == 1) {
      work_q_producer();
    } else if (warp == 2) {
      int left = SPIN_BUDGET;
      uint32_t passes = 0;
#pragma unroll 1
      for (int n = 0; n < 2 * NS; n++) {
        int l, s;
        if (w >= NP || !job_of<false>(n, l, s)) continue;
        pass_wait(passes += 8, left);
        if (elect()) cnt_signal(&g_cnt[CN_P][s][l * 32]);
        __syncwarp();
      }
    } else {
#pragma unroll 1
      for (int n = 0; n < 2 * (NS + 1); n++) {
        int l, s;
        if (!job_of<true>(n, l, s)) continue;
        bar_sync(NB_A, 160);
        if (elect()) cnt_signal(&g_cnt[CN_A][s][l * 32]);
        __syncwarp();
        if (w == WW && tid0 == 96 && (l == 0 || n >= 2 * NSEG)) WTS(n >> 1, 7);
      }
    }
  }
  asm volatile("griddepcontrol.wait;" ::: "memory");
}

typedef CUresult (*EncodeFn)(CUtensorMap*, CUtensorMapDataType, cuuint32_t, void*, const cuuint64_t*, const cuuint64_t*,
                             const cuuint32_t*, const cuuint32_t*, CUtensorMapInterleave, CUtensorMapSwizzle,
                             CUtensorMapL2promotion, CUtensorMapFloatOOBfill);

static void make_map(EncodeFn enc, CUtensorMap* tm, const void* ptr, uint64_t cols, uint64_t rows, uint32_t boxc, uint32_t boxr,
                     CUtensorMapSwizzle sw = CU_TENSOR_MAP_SWIZZLE_128B, CUtensorMapL2promotion pr = CU_TENSOR_MAP_L2_PROMOTION_L2_256B) {
  cuuint64_t dims[2] = {cols, rows};
  cuuint64_t strides[1] = {cols * 2};
  cuuint32_t box[2] = {boxc, boxr};
  cuuint32_t es[2] = {1, 1};
  enc(tm, CU_TENSOR_MAP_DATA_TYPE_BFLOAT16, 2, const_cast<void*>(ptr), dims, strides, box, es, CU_TENSOR_MAP_INTERLEAVE_NONE,
      sw, pr, CU_TENSOR_MAP_FLOAT_OOB_FILL_NONE);
}

extern "C" void kernel_launch(void* const* d_in, const int* in_sizes, int n_in, void* d_out, int out_size) {
  const bf16* x0 = (const bf16*)d_in[0];
  const bf16* mem0 = (const bf16*)d_in[1];
  const bf16* Wq = (const bf16*)d_in[2];
  const bf16* Wk = (const bf16*)d_in[3];
  const bf16* Wv = (const bf16*)d_in[4];
  const bf16* Wo = (const bf16*)d_in[5];
  const bf16* Bqkv = (const bf16*)d_in[8];
  const bf16* Bwo = (const bf16*)d_in[9];
  bf16* out = (bf16*)d_out;

  static EncodeFn enc = nullptr;
  static uint8_t *p_xn, *p_o, *p_mbuf, *p_mail, *p_rot;
  if (!enc) {
    void* fn = nullptr;
    cudaDriverEntryPointQueryResult qr;
    cudaGetDriverEntryPoint("cuTensorMapEncodeTiled", &fn, cudaEnableDefault, &qr);
    enc = (EncodeFn)fn;
    cudaFuncSetAttribute(k_chain, cudaFuncAttributeMaxDynamicSharedMemorySize, C::SMEM);
    cudaFuncSetAttribute(k_work, cudaFuncAttributeMaxDynamicSharedMemorySize, W::SMEM);
    void* p;
    cudaGetSymbolAddress(&p, g_xn); p_xn = (uint8_t*)p;
    cudaGetSymbolAddress(&p, g_o); p_o = (uint8_t*)p;
    cudaGetSymbolAddress(&p, g_mbuf); p_mbuf = (uint8_t*)p;
    cudaGetSymbolAddress(&p, g_mail); p_mail = (uint8_t*)p;
    cudaGetSymbolAddress(&p, g_rot); p_rot = (uint8_t*)p;
  }
  CUtensorMap tmWq, tmWk, tmWv, tmWo, tmWo16, tmBo, tmX;
  make_map(enc, &tmWq, Wq, NH * DH, DM, 64, 64);
  make_map(enc, &tmWk, Wk, NH * DH, DM, 64, 64);
  make_map(enc, &tmWv, Wv, NH * DH, DM, 64, 64);
  make_map(enc, &tmWo, Wo, DM, NH * DH, 64, 64);
  make_map(enc, &tmWo16, Wo, DM, NH * DH, 64, 16);
  make_map(enc, &tmBo, Bwo, DM, DM, 64, 16);
  {
    cuuint64_t dims[3] = {2560, 4 * NS, 2};
    cuuint64_t strides[2] = {10240, (cuuint64_t)(256 - 4 * LAG) * 10240};
    cuuint32_t box[3] = {256, 3, 2};
    cuuint32_t es[3] = {1, 1, 1};
    enc(&tmX, CU_TENSOR_MAP_DATA_TYPE_UINT32, 3, p_xn, dims, strides, box, es, CU_TENSOR_MAP_INTERLEAVE_NONE,
        CU_TENSOR_MAP_SWIZZLE_NONE, CU_TENSOR_MAP_L2_PROMOTION_NONE, CU_TENSOR_MAP_FLOAT_OOB_FILL_NONE);
  }

  cudaStream_t st = cudaStreamPerThread;
  k_pre<<<256, 256, 0, st>>>(x0, mem0);
  ChainArgs ca;
  ca.xn = p_xn;
  ca.oimg = p_o;
  ca.mbuf = p_mbuf; ca.mail = p_mail; ca.rot = p_rot;
  ca.ten = 10;
  fill_descs(ca);
  k_chain<<<96, 384, C::SMEM, st>>>(tmWq, tmWk, tmWv, tmWo, tmX, ca);
  WorkArgs wa;
  fill_descs(wa);
  wa.x0 = x0; wa.out = out;
  wa.wqkv = Bqkv;
  cudaLaunchAttribute at[1];
  at[0].id = cudaLaunchAttributeProgrammaticStreamSerialization; at[0].val.programmaticStreamSerializationAllowed = 1;
  cudaLaunchConfig_t cfg = {};
  cfg.gridDim = dim3(W::NW); cfg.blockDim = dim3(512); cfg.dynamicSmemBytes = W::SMEM; cfg.stream = st;
  cfg.attrs = at; cfg.numAttrs = 1;
  cudaLaunchKernelEx(&cfg, k_work, tmWo16, tmBo, wa);
}
```

```cpp
#include <cuda_runtime.h>
#include <cuda_bf16.h>
#include <cuda.h>
#include <stdint.h>

typedef __nv_bfloat16 bf16;

constexpr int SEQ = 2048, DM = 640, NH = 32, DH = 192, NSEG = 64;
#define LAG 6
constexpr int NS = NSEG + LAG;
constexpr uint32_t SENT = 0xFFFFFFFFu;
#define BUDGET_LOG 20
constexpr int SPIN_BUDGET = 1 << BUDGET_LOG;

constexpr int MD = LAG <= 4 ? 4 : 8;
static_assert(LAG <= 6, "depth of the rings");
constexpr int MAIL_UNIT = 65536, NUNIT = 88;
__device__ __align__(1024) uint8_t g_xn[2][32 * 10 * 8192];
__device__ __align__(1024) uint8_t g_xnb[8][81920];
__device__ __align__(1024) uint8_t g_ob[8][2][40960];
__device__ __align__(1024) uint8_t g_o[8][2][96][4096];
__device__ __align__(1024) uint8_t g_part[MD][2][16 * 2560];
__device__ __align__(1024) uint8_t g_prod[MD][2][16 * 2560];
__device__ __align__(131072) uint8_t g_mbuf[3][40960];
__device__ __align__(65536) uint8_t g_mail[NUNIT + 1][MAIL_UNIT];
__device__ __align__(1024) uint8_t g_rot[96][32768];
__device__ __align__(128) uint8_t g_xs[3][SEQ * DM * 2];
enum { CN_O = 0, CN_L = 1, CN_A = 2, CN_X = 3, CN_Z = 4, CN_P = 5, CN_S = 6 };
typedef uint32_t Counters[NS + 1][6 * 32];
__device__ __align__(128) Counters g_cnt[2][7];
__device__ uint32_t g_launch;
__device__ int g_err;
#define DUR(i)
#define TS(jj, i)
#define PTS(i)
#define PT2(i, t)
#define TSB(jj, i)
#define TSV(jj, i, v)
#define TS_FLUSH(jj)
#define WTS(i, k)
#define WW -1

__device__ __forceinline__ uint32_t smem_u32(const void* p) { return (uint32_t)__cvta_generic_to_shared(p); }
__device__ __forceinline__ uint32_t clk32() { unsigned long long t; asm volatile("mov.u64 %0, %%clock64;" : "=l"(t)::"memory"); return (uint32_t)t; }
__device__ __forceinline__ uint32_t mapa(uint32_t a, uint32_t r) { uint32_t o; asm("mapa.shared::cluster.u32 %0,%1,%2;" : "=r"(o) : "r"(a), "r"(r)); return o; }
__device__ __forceinline__ void mbar_init(uint32_t bar, uint32_t cnt) { asm volatile("mbarrier.init.shared::cta.b64 [%0],%1;" ::"r"(bar), "r"(cnt) : "memory"); }
__device__ __forceinline__ void mbar_expect_tx(uint32_t bar, uint32_t bytes) { asm volatile("mbarrier.arrive.expect_tx.shared::cta.b64 _,[%0],%1;" ::"r"(bar), "r"(bytes) : "memory"); }
__device__ __forceinline__ void mbar_arrive(uint32_t bar) { asm volatile("mbarrier.arrive.shared::cta.b64 _,[%0];" ::"r"(bar) : "memory"); }
__device__ __forceinline__ void mbar_arrive_cluster(uint32_t bar) { asm volatile("mbarrier.arrive.shared::cluster.b64 _,[%0];" ::"r"(bar) : "memory"); }
__device__ __forceinline__ bool mbar_try(uint32_t bar, uint32_t ph) {
  uint32_t ok;
  asm volatile("{.reg .pred p; mbarrier.try_wait.parity.shared::cta.b64 p,[%1],%2; selp.u32 %0,1,0,p;}" : "=r"(ok) : "r"(bar), "r"(ph) : "memory");
  return ok;
}
__device__ __forceinline__ bool mbar_test(uint32_t bar, uint32_t ph) {
  uint32_t ok;
  asm volatile("{.reg .pred p; mbarrier.test_wait.parity.shared::cta.b64 p,[%1],%2; selp.u32 %0,1,0,p;}" : "=r"(ok) : "r"(bar), "r"(ph) : "memory");
  return ok;
}
__device__ __forceinline__ void mbar_wait(uint32_t bar, uint32_t ph, int& left) {
  asm volatile("{\n.reg .pred p;\nW: mbarrier.try_wait.parity.shared::cta.b64 p,[%1],%2;\nadd.s32 %0,%0,-1;\nsetp.gt.and.s32 p,%0,0,!p;\n@p bra.uni W;\n}"
               : "+r"(left) : "r"(bar), "r"(ph) : "memory");
}
__device__ __forceinline__ bool elect() {
  uint32_t p;
  asm volatile("{.reg .pred p; elect.sync _|p,0xffffffff; selp.u32 %0,1,0,p;}" : "=r"(p));
  return p;
}
__device__ __forceinline__ int fresh(int x) { asm volatile("" : "+r"(x)); return x; }
__device__ __forceinline__ void bar_sync(int id, int n) { asm volatile("bar.sync %0,%1;" ::"r"(id), "r"(n) : "memory"); }
__device__ __forceinline__ void bar_arrive(int id, int n) { asm volatile("bar.arrive %0,%1;" ::"r"(id), "r"(n) : "memory"); }
__device__ __forceinline__ bool bar_red_or(int id, int n, bool v) {
  uint32_t r;
  asm volatile("{\n .reg .pred p, q;\n setp.ne.u32 q, %3, 0;\n barrier.cta.red.or.pred p, %1, %2, q;\n selp.u32 %0, 1, 0, p;\n}" : "=r"(r) : "r"(id), "r"(n), "r"((uint32_t)v) : "memory");
  return r != 0;
}
__device__ __forceinline__ void cluster_sync() {
  asm volatile("barrier.cluster.arrive.release.aligned;" ::: "memory");
  asm volatile("barrier.cluster.wait.acquire.aligned;" ::: "memory");
}
__device__ __forceinline__ void cluster_sync_relaxed() {
  asm volatile("barrier.cluster.arrive.relaxed.aligned;" ::: "memory");
  asm volatile("barrier.cluster.wait.aligned;" ::: "memory");
}
__device__ __forceinline__ void fence_async() { asm volatile("fence.proxy.async.shared::cta;" ::: "memory"); }
__device__ __forceinline__ void bulk_g2s(uint32_t dst, const void* src, uint32_t bytes, uint32_t bar) {
  asm volatile("cp.async.bulk.shared::cluster.global.mbarrier::complete_tx::bytes [%0],[%1],%2,[%3];" ::"r"(dst), "l"(src), "r"(bytes), "r"(bar) : "memory");
}
__device__ __forceinline__ void bulk_g2s_mc(uint32_t dst, const void* src, uint32_t bytes, uint32_t bar) {
  asm volatile("cp.async.bulk.shared::cluster.global.mbarrier::complete_tx::bytes.multicast::cluster [%0],[%1],%2,[%3],%4;"
               ::"r"(dst), "l"(src), "r"(bytes), "r"(bar), "h"((uint16_t)7) : "memory");
}
__device__ __forceinline__ void bulk_s2g(void* dst, uint32_t src, uint32_t bytes) {
  asm volatile("cp.async.bulk.global.shared::cta.bulk_group [%0],[%1],%2;" ::"l"(dst), "r"(src), "r"(bytes) : "memory");
}
__device__ __forceinline__ void bulk_s2c(uint32_t dst, uint32_t src, uint32_t bytes, uint32_t bar) {
  asm volatile("cp.async.bulk.shared::cluster.shared::cta.mbarrier::complete_tx::bytes [%0],[%1],%2,[%3];" ::"r"(dst), "r"(src), "r"(bytes), "r"(bar) : "memory");
}
__device__ __forceinline__ void bulk_commit() { asm volatile("cp.async.bulk.commit_group;" ::: "memory"); }
__device__ __forceinline__ void bulk_wait_read() { asm volatile("cp.async.bulk.wait_group.read 0;" ::: "memory"); }
__device__ __forceinline__ void bulk_wait() { asm volatile("cp.async.bulk.wait_group 0;" ::: "memory"); }
__device__ __forceinline__ void tma2d(uint32_t dst, const CUtensorMap* tm, int c0, int c1, uint32_t bar) {
  asm volatile("cp.async.bulk.tensor.2d.shared::cluster.global.mbarrier::complete_tx::bytes [%0],[%1,{%3,%4}],[%2];"
               ::"r"(dst), "l"(tm), "r"(bar), "r"(c0), "r"(c1) : "memory");
}
__device__ __forceinline__ void tma2d_prefetch(const CUtensorMap* tm, int c0, int c1) {
  asm volatile("cp.async.bulk.prefetch.tensor.2d.L2.global.tile [%0,{%1,%2}];" ::"l"(tm), "r"(c0), "r"(c1) : "memory");
}
__device__ __forceinline__ void tma3d_mc(uint32_t dst, const CUtensorMap* tm, int c0, int c1, int c2, uint32_t bar) {
  asm volatile("cp.async.bulk.tensor.3d.shared::cluster.global.mbarrier::complete_tx::bytes.multicast::cluster [%0],[%1,{%3,%4,%5}],[%2],%6;"
               ::"r"(dst), "l"(tm), "r"(bar), "r"(c0), "r"(c1), "r"(c2), "h"((uint16_t)7) : "memory");
}
__device__ __forceinline__ uint32_t pack_bf16(float lo, float hi) {
  uint32_t r; asm("cvt.rn.bf16x2.f32 %0,%1,%2;" : "=r"(r) : "f"(hi), "f"(lo)); return r;
}
__device__ __forceinline__ uint32_t pack_h2(float lo, float hi) {
  uint32_t r; asm("cvt.rn.satfinite.f16x2.f32 %0,%1,%2;" : "=r"(r) : "f"(hi), "f"(lo)); return r;
}
__device__ __forceinline__ float2 unpack_h2(uint32_t x) {
  float2 r; asm("{.reg .b16 l,h; mov.b32 {l,h},%2; cvt.f32.f16 %0,l; cvt.f32.f16 %1,h;}" : "=f"(r.x), "=f"(r.y) : "r"(x)); return r;
}
__device__ __forceinline__ uint32_t add_h2(uint32_t a, uint32_t b) { uint32_t r; asm("add.rn.f16x2 %0,%1,%2;" : "=r"(r) : "r"(a), "r"(b)); return r; }
__device__ __forceinline__ uint32_t max_h2(uint32_t a, uint32_t b) { uint32_t r; asm("max.f16x2 %0,%1,%2;" : "=r"(r) : "r"(a), "r"(b)); return r; }
__device__ __forceinline__ float bf_lo(uint32_t x) { return __uint_as_float(x << 16); }
__device__ __forceinline__ float bf_hi(uint32_t x) { return __uint_as_float(x & 0xFFFF0000u); }
__device__ __forceinline__ float ex2(float x) { float y; asm("ex2.approx.ftz.f32 %0,%1;" : "=f"(y) : "f"(x)); return y; }
__device__ __forceinline__ void ldsm4t(uint32_t (&r)[4], uint32_t a) {
  asm volatile("ldmatrix.sync.aligned.m8n8.x4.trans.shared.b16 {%0,%1,%2,%3},[%4];" : "=r"(r[0]), "=r"(r[1]), "=r"(r[2]), "=r"(r[3]) : "r"(a) : "memory");
}
__device__ __forceinline__ void stsm4(uint32_t a, uint32_t r0, uint32_t r1, uint32_t r2, uint32_t r3) {
  asm volatile("stmatrix.sync.aligned.m8n8.x4.shared.b16 [%0],{%1,%2,%3,%4};" ::"r"(a), "r"(r0), "r"(r1), "r"(r2), "r"(r3) : "memory");
}
__device__ __forceinline__ void stsm4t(uint32_t a, uint32_t r0, uint32_t r1, uint32_t r2, uint32_t r3) {
  asm volatile("stmatrix.sync.aligned.m8n8.x4.trans.shared.b16 [%0],{%1,%2,%3,%4};" ::"r"(a), "r"(r0), "r"(r1), "r"(r2), "r"(r3) : "memory");
}
__device__ __forceinline__ void stsm2(uint32_t a, uint32_t r0, uint32_t r1) {
  asm volatile("stmatrix.sync.aligned.m8n8.x2.shared.b16 [%0],{%1,%2};" ::"r"(a), "r"(r0), "r"(r1) : "memory");
}
__device__ __forceinline__ void sts32(uint32_t a, uint32_t v) { asm volatile("st.shared.b32 [%0],%1;" ::"r"(a), "r"(v) : "memory"); }
__device__ __forceinline__ void sts128(uint32_t a, uint4 v) { asm volatile("st.shared.v4.b32 [%0],{%1,%2,%3,%4};" ::"r"(a), "r"(v.x), "r"(v.y), "r"(v.z), "r"(v.w) : "memory"); }
__device__ __forceinline__ uint32_t lds32(uint32_t a) { uint32_t v; asm volatile("ld.shared.b32 %0,[%1];" : "=r"(v) : "r"(a) : "memory"); return v; }
__device__ __forceinline__ uint2 lds64(uint32_t a) { uint2 v; asm volatile("ld.shared.v2.b32 {%0,%1},[%2];" : "=r"(v.x), "=r"(v.y) : "r"(a) : "memory"); return v; }
__device__ __forceinline__ uint4 lds128(uint32_t a) { uint4 v; asm volatile("ld.shared.v4.b32 {%0,%1,%2,%3},[%4];" : "=r"(v.x), "=r"(v.y), "=r"(v.z), "=r"(v.w) : "r"(a) : "memory"); return v; }
__device__ __forceinline__ void st_async1(uint32_t a, uint32_t x, uint32_t bar) {
  asm volatile("st.async.weak.shared::cluster.mbarrier::complete_tx::bytes.b32 [%0],%1,[%2];" ::"r"(a), "r"(x), "r"(bar) : "memory");
}
__device__ __forceinline__ void st_async2(uint32_t a, uint32_t x, uint32_t y, uint32_t bar) {
  asm volatile("st.async.weak.shared::cluster.mbarrier::complete_tx::bytes.v2.b32 [%0],{%1,%2},[%3];" ::"r"(a), "r"(x), "r"(y), "r"(bar) : "memory");
}
__device__ __forceinline__ void st_async4(uint32_t a, uint32_t x, uint32_t y, uint32_t z, uint32_t w, uint32_t bar) {
  asm volatile("st.async.weak.shared::cluster.mbarrier::complete_tx::bytes.v4.b32 [%0],{%1,%2,%3,%4},[%5];" ::"r"(a), "r"(x), "r"(y), "r"(z), "r"(w), "r"(bar) : "memory");
}
__device__ __forceinline__ uint32_t ld_relaxed(const void* p) {
  uint32_t v; asm volatile("ld.relaxed.gpu.global.u32 %0,[%1];" : "=r"(v) : "l"(p) : "memory"); return v;
}
__device__ __forceinline__ void st_relaxed(void* p, uint32_t v) { asm volatile("st.relaxed.gpu.global.b32 [%0],%1;" ::"l"(p), "r"(v) : "memory"); }
__device__ __forceinline__ void ld_msg16x4(uint4* x, const void* p) {
  asm volatile("{.reg .b128 a,b,c,d;\n ld.relaxed.gpu.global.b128 a,[%16]; ld.relaxed.gpu.global.b128 b,[%16+512];\n"
               "ld.relaxed.gpu.global.b128 c,[%16+1024]; ld.relaxed.gpu.global.b128 d,[%16+1536];\n"
               "mov.b128 {%0,%1,%2,%3},a; mov.b128 {%4,%5,%6,%7},b; mov.b128 {%8,%9,%10,%11},c; mov.b128 {%12,%13,%14,%15},d;}"
               : "=r"(x[0].x), "=r"(x[0].y), "=r"(x[0].z), "=r"(x[0].w), "=r"(x[1].x), "=r"(x[1].y), "=r"(x[1].z), "=r"(x[1].w),
                 "=r"(x[2].x), "=r"(x[2].y), "=r"(x[2].z), "=r"(x[2].w), "=r"(x[3].x), "=r"(x[3].y), "=r"(x[3].z), "=r"(x[3].w)
               : "l"(p) : "memory");
}
__device__ __forceinline__ uint32_t differ4(uint32_t a, uint32_t b, uint32_t c, uint32_t d, uint32_t t) {
  uint32_t r;
  asm volatile("{.reg .b32 u,v; lop3.b32 u,%1,%2,%5,0x7e; lop3.b32 v,%3,%4,%5,0x7e; or.b32 %0,u,v;}" : "=r"(r) : "r"(a), "r"(b), "r"(c), "r"(d), "r"(t));
  return r;
}
__device__ __forceinline__ void st_msg16(void* p, uint32_t x, uint32_t y, uint32_t z, uint32_t w) {
  asm volatile("{.reg .b128 r; mov.b128 r,{%1,%2,%3,%4}; st.relaxed.gpu.global.b128 [%0],r;}" ::"l"(p), "r"(x), "r"(y), "r"(z), "r"(w) : "memory");
}
__device__ __forceinline__ void ld_msg16x2(uint4* x, const void* p) {
  asm volatile("{.reg .b128 a,b;\n ld.relaxed.gpu.global.b128 a,[%8]; ld.relaxed.gpu.global.b128 b,[%8+512];\n"
               "mov.b128 {%0,%1,%2,%3},a; mov.b128 {%4,%5,%6,%7},b;}"
               : "=r"(x[0].x), "=r"(x[0].y), "=r"(x[0].z), "=r"(x[0].w), "=r"(x[1].x), "=r"(x[1].y), "=r"(x[1].z), "=r"(x[1].w)
               : "l"(p) : "memory");
}
__device__ __forceinline__ void ld_msg16x6(uint4* x, const void* p, const void* q) {
  asm volatile("{.reg .b128 a,b,c,d,e,f;\n ld.relaxed.gpu.global.b128 a,[%24]; ld.relaxed.gpu.global.b128 b,[%24+512];\n"
               "ld.relaxed.gpu.global.b128 c,[%24+1024]; ld.relaxed.gpu.global.b128 d,[%24+1536];\n"
               "ld.relaxed.gpu.global.b128 e,[%25]; ld.relaxed.gpu.global.b128 f,[%25+512];\n"
               "mov.b128 {%0,%1,%2,%3},a; mov.b128 {%4,%5,%6,%7},b; mov.b128 {%8,%9,%10,%11},c; mov.b128 {%12,%13,%14,%15},d;\n"
               "mov.b128 {%16,%17,%18,%19},e; mov.b128 {%20,%21,%22,%23},f;}"
               : "=r"(x[0].x), "=r"(x[0].y), "=r"(x[0].z), "=r"(x[0].w), "=r"(x[1].x), "=r"(x[1].y), "=r"(x[1].z), "=r"(x[1].w),
                 "=r"(x[2].x), "=r"(x[2].y), "=r"(x[2].z), "=r"(x[2].w), "=r"(x[3].x), "=r"(x[3].y), "=r"(x[3].z), "=r"(x[3].w),
                 "=r"(x[4].x), "=r"(x[4].y), "=r"(x[4].z), "=r"(x[4].w), "=r"(x[5].x), "=r"(x[5].y), "=r"(x[5].z), "=r"(x[5].w)
               : "l"(p), "l"(q) : "memory");
}
__device__ __forceinline__ uint32_t ld_acquire(const void* p) {
  uint32_t v; asm volatile("ld.acquire.gpu.global.u32 %0,[%1];" : "=r"(v) : "l"(p) : "memory"); return v;
}
__device__ __forceinline__ float4 ld_relaxed4f(const void* p) {
  float4 v; asm volatile("ld.relaxed.gpu.global.v4.f32 {%0,%1,%2,%3},[%4];" : "=f"(v.x), "=f"(v.y), "=f"(v.z), "=f"(v.w) : "l"(p) : "memory"); return v;
}
__device__ __forceinline__ float2 ld_relaxed2f(const void* p) {
  float2 v; asm volatile("ld.relaxed.gpu.global.v2.f32 {%0,%1},[%2];" : "=f"(v.x), "=f"(v.y) : "l"(p) : "memory"); return v;
}
__device__ __forceinline__ uint4 ld_nc16(const void* p) {
  uint4 v; asm volatile("ld.global.nc.v4.u32 {%0,%1,%2,%3},[%4];" : "=r"(v.x), "=r"(v.y), "=r"(v.z), "=r"(v.w) : "l"(p)); return v;
}
__device__ __forceinline__ void prefetch_l2(const void* p) { asm volatile("prefetch.global.L2 [%0];" ::"l"(p)); }
__device__ __forceinline__ void fence_async_all() { asm volatile("fence.proxy.async.global;" ::: "memory"); }
__device__ __forceinline__ int launch_parity() { return __shfl_sync(0xffffffffu, ld_relaxed(&g_launch) & 1, 0); }
__device__ __forceinline__ void cnt_wait_warp(const uint32_t* p, uint32_t target, int& left) {
  while (__any_sync(0xffffffffu, ld_acquire(p) < target) && (left -= 16) > 0) {}
}
__device__ __forceinline__ void cnt_signal(uint32_t* p) { asm volatile("red.release.gpu.global.add.u32 [%0],1;" ::"l"(p) : "memory"); }

__host__ __device__ __forceinline__ constexpr uint64_t mkdesc(uint32_t addr, uint32_t lbo, uint32_t sbo) {
  return (uint64_t)((addr & 0x3FFFF) >> 4) | ((uint64_t)(lbo >> 4) << 16) | ((uint64_t)(sbo >> 4) << 32) | ((uint64_t)1 << 62);
}
__host__ __device__ __forceinline__ constexpr uint64_t mkdesc64(uint32_t addr, uint32_t lbo, uint32_t sbo) {
  return (uint64_t)((addr & 0x3FFFF) >> 4) | ((uint64_t)(lbo >> 4) << 16) | ((uint64_t)(sbo >> 4) << 32) | ((uint64_t)2 << 62);
}
__host__ __device__ __forceinline__ constexpr uint64_t mkdesc_ns(uint32_t addr, uint32_t lbo, uint32_t sbo) {
  return (uint64_t)((addr & 0x3FFFF) >> 4) | ((uint64_t)(lbo >> 4) << 16) | ((uint64_t)(sbo >> 4) << 32);
}
__device__ __forceinline__ void wg_fence() { asm volatile("wgmma.fence.sync.aligned;" ::: "memory"); }
__device__ __forceinline__ void wg_commit() { asm volatile("wgmma.commit_group.sync.aligned;" ::: "memory"); }
template <int N> __device__ __forceinline__ void wg_wait() { asm volatile("wgmma.wait_group.sync.aligned %0;" ::"n"(N) : "memory"); }

__device__ __forceinline__ void wgmma_rs32(float (&d)[16], const uint32_t (&a)[4], uint64_t db, int sc) {
  asm volatile("{.reg .pred p; setp.ne.b32 p,%21,0; wgmma.mma_async.sync.aligned.m64n32k16.f32.bf16.bf16 "
               "{%0,%1,%2,%3,%4,%5,%6,%7,%8,%9,%10,%11,%12,%13,%14,%15},{%16,%17,%18,%19},%20,p,1,1,0;}"
               : "+f"(d[0]), "+f"(d[1]), "+f"(d[2]), "+f"(d[3]), "+f"(d[4]), "+f"(d[5]), "+f"(d[6]), "+f"(d[7]),
                 "+f"(d[8]), "+f"(d[9]), "+f"(d[10]), "+f"(d[11]), "+f"(d[12]), "+f"(d[13]), "+f"(d[14]), "+f"(d[15])
               : "r"(a[0]), "r"(a[1]), "r"(a[2]), "r"(a[3]), "l"(db), "r"(sc));
}
__device__ __forceinline__ void wgmma_rt32(float (&d)[16], const uint32_t (&a)[4], uint64_t db, int sc) {
  asm volatile("{.reg .pred p; setp.ne.b32 p,%21,0; wgmma.mma_async.sync.aligned.m64n32k16.f32.bf16.bf16 "
               "{%0,%1,%2,%3,%4,%5,%6,%7,%8,%9,%10,%11,%12,%13,%14,%15},{%16,%17,%18,%19},%20,p,1,1,1;}"
               : "+f"(d[0]), "+f"(d[1]), "+f"(d[2]), "+f"(d[3]), "+f"(d[4]), "+f"(d[5]), "+f"(d[6]), "+f"(d[7]),
                 "+f"(d[8]), "+f"(d[9]), "+f"(d[10]), "+f"(d[11]), "+f"(d[12]), "+f"(d[13]), "+f"(d[14]), "+f"(d[15])
               : "r"(a[0]), "r"(a[1]), "r"(a[2]), "r"(a[3]), "l"(db), "r"(sc));
}
__device__ __forceinline__ void wgmma_rs48(float (&d)[24], const uint32_t (&a)[4], uint64_t db, int sc) {
  asm volatile("{.reg .pred p; setp.ne.b32 p,%29,0; wgmma.mma_async.sync.aligned.m64n48k16.f32.bf16.bf16 "
               "{%0,%1,%2,%3,%4,%5,%6,%7,%8,%9,%10,%11,%12,%13,%14,%15,%16,%17,%18,%19,%20,%21,%22,%23},{%24,%25,%26,%27},%28,p,1,1,0;}"
               : "+f"(d[0]), "+f"(d[1]), "+f"(d[2]), "+f"(d[3]), "+f"(d[4]), "+f"(d[5]), "+f"(d[6]), "+f"(d[7]),
                 "+f"(d[8]), "+f"(d[9]), "+f"(d[10]), "+f"(d[11]), "+f"(d[12]), "+f"(d[13]), "+f"(d[14]), "+f"(d[15]),
                 "+f"(d[16]), "+f"(d[17]), "+f"(d[18]), "+f"(d[19]), "+f"(d[20]), "+f"(d[21]), "+f"(d[22]), "+f"(d[23])
               : "r"(a[0]), "r"(a[1]), "r"(a[2]), "r"(a[3]), "l"(db), "r"(sc));
}
__device__ __forceinline__ void wgmma_ts32(float (&d)[16], uint64_t da, uint64_t db, int sc) {
  asm volatile("{.reg .pred p; setp.ne.b32 p,%18,0; wgmma.mma_async.sync.aligned.m64n32k16.f32.bf16.bf16 "
               "{%0,%1,%2,%3,%4,%5,%6,%7,%8,%9,%10,%11,%12,%13,%14,%15},%16,%17,p,1,1,1,0;}"
               : "+f"(d[0]), "+f"(d[1]), "+f"(d[2]), "+f"(d[3]), "+f"(d[4]), "+f"(d[5]), "+f"(d[6]), "+f"(d[7]),
                 "+f"(d[8]), "+f"(d[9]), "+f"(d[10]), "+f"(d[11]), "+f"(d[12]), "+f"(d[13]), "+f"(d[14]), "+f"(d[15])
               : "l"(da), "l"(db), "r"(sc));
}
__device__ __forceinline__ void wgmma_tt32(float (&d)[16], uint64_t da, uint64_t db, int sc) {
  asm volatile("{.reg .pred p; setp.ne.b32 p,%18,0; wgmma.mma_async.sync.aligned.m64n32k16.f32.bf16.bf16 "
               "{%0,%1,%2,%3,%4,%5,%6,%7,%8,%9,%10,%11,%12,%13,%14,%15},%16,%17,p,1,1,1,1;}"
               : "+f"(d[0]), "+f"(d[1]), "+f"(d[2]), "+f"(d[3]), "+f"(d[4]), "+f"(d[5]), "+f"(d[6]), "+f"(d[7]),
                 "+f"(d[8]), "+f"(d[9]), "+f"(d[10]), "+f"(d[11]), "+f"(d[12]), "+f"(d[13]), "+f"(d[14]), "+f"(d[15])
               : "l"(da), "l"(db), "r"(sc));
}
__device__ __forceinline__ void wgmma_ts48(float (&d)[24], uint64_t da, uint64_t db, int sc) {
  asm volatile("{.reg .pred p; setp.ne.b32 p,%26,0; wgmma.mma_async.sync.aligned.m64n48k16.f32.bf16.bf16 "
               "{%0,%1,%2,%3,%4,%5,%6,%7,%8,%9,%10,%11,%12,%13,%14,%15,%16,%17,%18,%19,%20,%21,%22,%23},%24,%25,p,1,1,1,0;}"
               : "+f"(d[0]), "+f"(d[1]), "+f"(d[2]), "+f"(d[3]), "+f"(d[4]), "+f"(d[5]), "+f"(d[6]), "+f"(d[7]),
                 "+f"(d[8]), "+f"(d[9]), "+f"(d[10]), "+f"(d[11]), "+f"(d[12]), "+f"(d[13]), "+f"(d[14]), "+f"(d[15]),
                 "+f"(d[16]), "+f"(d[17]), "+f"(d[18]), "+f"(d[19]), "+f"(d[20]), "+f"(d[21]), "+f"(d[22]), "+f"(d[23])
               : "l"(da), "l"(db), "r"(sc));
}
__device__ __forceinline__ void wgmma_ts64(float (&d)[32], uint64_t da, uint64_t db, int sc) {
  asm volatile("{.reg .pred p; setp.ne.b32 p,%34,0; wgmma.mma_async.sync.aligned.m64n64k16.f32.bf16.bf16 "
               "{%0,%1,%2,%3,%4,%5,%6,%7,%8,%9,%10,%11,%12,%13,%14,%15,%16,%17,%18,%19,%20,%21,%22,%23,%24,%25,%26,%27,%28,%29,%30,%31},%32,%33,p,1,1,1,0;}"
               : "+f"(d[0]), "+f"(d[1]), "+f"(d[2]), "+f"(d[3]), "+f"(d[4]), "+f"(d[5]), "+f"(d[6]), "+f"(d[7]),
                 "+f"(d[8]), "+f"(d[9]), "+f"(d[10]), "+f"(d[11]), "+f"(d[12]), "+f"(d[13]), "+f"(d[14]), "+f"(d[15]),
                 "+f"(d[16]), "+f"(d[17]), "+f"(d[18]), "+f"(d[19]), "+f"(d[20]), "+f"(d[21]), "+f"(d[22]), "+f"(d[23]),
                 "+f"(d[24]), "+f"(d[25]), "+f"(d[26]), "+f"(d[27]), "+f"(d[28]), "+f"(d[29]), "+f"(d[30]), "+f"(d[31])
               : "l"(da), "l"(db), "r"(sc));
}
__device__ __forceinline__ void wgmma_tt40(float (&d)[20], uint64_t da, uint64_t db, int sc) {
  asm volatile("{.reg .pred p; setp.ne.b32 p,%22,0; wgmma.mma_async.sync.aligned.m64n40k16.f32.bf16.bf16 "
               "{%0,%1,%2,%3,%4,%5,%6,%7,%8,%9,%10,%11,%12,%13,%14,%15,%16,%17,%18,%19},%20,%21,p,1,1,1,1;}"
               : "+f"(d[0]), "+f"(d[1]), "+f"(d[2]), "+f"(d[3]), "+f"(d[4]), "+f"(d[5]), "+f"(d[6]), "+f"(d[7]),
                 "+f"(d[8]), "+f"(d[9]), "+f"(d[10]), "+f"(d[11]), "+f"(d[12]), "+f"(d[13]), "+f"(d[14]), "+f"(d[15]),
                 "+f"(d[16]), "+f"(d[17]), "+f"(d[18]), "+f"(d[19])
               : "l"(da), "l"(db), "r"(sc));
}
__device__ __forceinline__ void wgmma_ss8(float (&d)[4], uint64_t da, uint64_t db, int sc) {
  asm volatile("{.reg .pred p; setp.ne.b32 p,%6,0; wgmma.mma_async.sync.aligned.m64n8k16.f32.bf16.bf16 "
               "{%0,%1,%2,%3},%4,%5,p,1,1,0,0;}"
               : "+f"(d[0]), "+f"(d[1]), "+f"(d[2]), "+f"(d[3])
               : "l"(da), "l"(db), "r"(sc));
}
__device__ __forceinline__ void wgmma_ss32(float (&d)[16], uint64_t da, uint64_t db, int sc) {
  asm volatile("{.reg .pred p; setp.ne.b32 p,%18,0; wgmma.mma_async.sync.aligned.m64n32k16.f32.bf16.bf16 "
               "{%0,%1,%2,%3,%4,%5,%6,%7,%8,%9,%10,%11,%12,%13,%14,%15},%16,%17,p,1,1,0,0;}"
               : "+f"(d[0]), "+f"(d[1]), "+f"(d[2]), "+f"(d[3]), "+f"(d[4]), "+f"(d[5]), "+f"(d[6]), "+f"(d[7]),
                 "+f"(d[8]), "+f"(d[9]), "+f"(d[10]), "+f"(d[11]), "+f"(d[12]), "+f"(d[13]), "+f"(d[14]), "+f"(d[15])
               : "l"(da), "l"(db), "r"(sc));
}
__device__ __forceinline__ void wgmma_tt16(float (&d)[8], uint64_t da, uint64_t db, int sc) {
  asm volatile("{.reg .pred p; setp.ne.b32 p,%10,0; wgmma.mma_async.sync.aligned.m64n16k16.f32.bf16.bf16 "
               "{%0,%1,%2,%3,%4,%5,%6,%7},%8,%9,p,1,1,1,1;}"
               : "+f"(d[0]), "+f"(d[1]), "+f"(d[2]), "+f"(d[3]), "+f"(d[4]), "+f"(d[5]), "+f"(d[6]), "+f"(d[7])
               : "l"(da), "l"(db), "r"(sc));
}

__device__ __forceinline__ void ln_row_load(const bf16* __restrict__ x, uint4 (&v)[3], int row, int lane) {
  const uint4* src = reinterpret_cast<const uint4*>(x + (size_t)row * DM);
  v[0] = ld_nc16(src + lane); v[1] = ld_nc16(src + lane + 32); v[2] = ld_nc16(src + 64 + (lane & 15));
}
__device__ __forceinline__ void ln_row(uint4 (&v)[3], int lane) {
  if (lane >= 16) v[2] = make_uint4(0, 0, 0, 0);
  float s = 0.f;
#pragma unroll
  for (int i = 0; i < 3; i++) {
    s += bf_lo(v[i].x) + bf_hi(v[i].x) + bf_lo(v[i].y) + bf_hi(v[i].y) + bf_lo(v[i].z) + bf_hi(v[i].z) + bf_lo(v[i].w) + bf_hi(v[i].w);
  }
#pragma unroll
  for (int o = 16; o > 0; o >>= 1) s += __shfl_xor_sync(0xffffffffu, s, o);
  const float mean = s * (1.f / DM);
  float q = 0.f;
#pragma unroll
  for (int i = 0; i < 3; i++) {
    if (i < 2 || lane < 16) {
      const uint32_t w[4] = {v[i].x, v[i].y, v[i].z, v[i].w};
#pragma unroll
      for (int j = 0; j < 4; j++) { float a = bf_lo(w[j]) - mean, b = bf_hi(w[j]) - mean; q += a * a + b * b; }
    }
  }
#pragma unroll
  for (int o = 16; o > 0; o >>= 1) q += __shfl_xor_sync(0xffffffffu, q, o);
  const float rstd = rsqrtf(q * (1.f / DM) + 1e-5f);
#pragma unroll
  for (int i = 0; i < 3; i++) {
    if (i < 2 || lane < 16) {
      uint4 o;
      o.x = pack_bf16((bf_lo(v[i].x) - mean) * rstd, (bf_hi(v[i].x) - mean) * rstd);
      o.y = pack_bf16((bf_lo(v[i].y) - mean) * rstd, (bf_hi(v[i].y) - mean) * rstd);
      o.z = pack_bf16((bf_lo(v[i].z) - mean) * rstd, (bf_hi(v[i].z) - mean) * rstd);
      o.w = pack_bf16((bf_lo(v[i].w) - mean) * rstd, (bf_hi(v[i].w) - mean) * rstd);
      v[i] = o;
    }
  }
}

namespace C {
constexpr int OFF_WK = 0;
constexpr int OFF_WO = 81920;
constexpr int OFF_WXQ = 131072;
constexpr int OFF_WXV = 133120;
constexpr int STAGE_Q = 51200, STAGE_V = 133120, STAGE_X = 215040;
constexpr int OFF_R = 139264;
constexpr int OFF_OG = OFF_R + 16384;
constexpr int OFF_RING = 180224;
constexpr int OFF_SCR = OFF_RING + 49152;
constexpr int SLOT = 6144;
__host__ __device__ constexpr int slot_off(int c) { return c < 3 ? OFF_R + 22528 + c * SLOT : c < 6 ? OFF_RING + (c - 3) * SLOT : OFF_RING + 20480 + (c - 6) * SLOT; }
constexpr int OFF_QT = OFF_RING;
constexpr int OFF_KT = OFF_RING + 10240;
constexpr int OFF_VT = OFF_RING + 20480;
constexpr int OFF_P = OFF_RING + 30720;
constexpr int OFF_XL = OFF_P + 7680;
constexpr int OFF_XM = OFF_XL + 10752;
__host__ __device__ constexpr int xl_off(int w) { return OFF_XL + (w ? w * 1152 - 512 : 0); }
constexpr int OFF_BAR = 231424;
constexpr int OFF_TS = OFF_BAR + 256;
constexpr int SMEM = 232448;
constexpr uint32_t SB0 = 1024;
constexpr int BAR_F0 = OFF_BAR, BAR_F1 = OFF_BAR + 8, BAR_F2 = OFF_BAR + 16,
              BAR_W1 = OFF_BAR + 80, BAR_W2 = OFF_BAR + 88, BAR_W3 = OFF_BAR + 96, BAR_X = OFF_BAR + 32,
              BAR_OG2 = OFF_BAR + 104, BAR_XE = OFF_BAR + 112,
              BAR_OG = OFF_BAR + 120, BAR_OE = OFF_BAR + 128, BAR_ROT = OFF_BAR + 136, BAR_RQ = OFF_BAR + 168, BAR_VF = OFF_BAR + 144, BAR_RF = OFF_BAR + 152,
              BAR_RE = OFF_BAR + 160, BAR_RID = OFF_BAR + 24, BAR_M = OFF_BAR + 176,
              OFF_SEL = OFF_BAR + 208;
constexpr int NB_M = 1, NB_QK = 2, NB_P = 3, NB_V = 4, NB_MR = 5, NB_GO = 6, NB_O = 7, NB_BQ = 8, NB_BV = 9, NB_S = 10, NB_X = 11, NB_M2 = 15;
#define B1 300
#define B2 400
#define B3 1500
#define OSP 0
#define PL2 1
#define PL1 1
#define OGF 1
#define PFD 3
constexpr float SCL = 0.07216878364870322f * 1.4426950408889634f;
__host__ __device__ constexpr int wo_off(int u) { return u < 2 ? OFF_RING + u * 8192 : u < 8 ? OFF_WO + (u - 2) * 8192 : OFF_R + (u - 8) * 8192; }
__host__ __device__ constexpr int wo_col(int u, int rank) { return u == 0 ? 576 : (3 * rank + (u - 1) % 3) * 64; }
__host__ __device__ constexpr int wo_row(int u, int cta) { return (cta / 3) * DH + ((cta + 3 - (u ? (u - 1) / 3 : 0)) % 3) * 64; }
}

struct ChainArgs {
  const bf16 *x0, *mem0, *wo;
  uint8_t* xn;
  uint8_t* oimg;
  uint8_t* mbuf;
  uint8_t* mail;
  uint8_t* rot;
  int ten;
  uint64_t td[40], rd[40], kd[44], od[40], gd[12], sd[16], vd[5], pd[12];
};

template <int NK>
__device__ __forceinline__ void load_wfrags(uint32_t (&a)[NK][4], uint32_t base, int w, int lane) {
  const int i = lane >> 3, r = lane & 7;
  const int chunk = 2 * w + (i & 1);
  const uint32_t a0 = base + (r + (i >> 1) * 8) * 128 + ((chunk ^ r) << 4);
#pragma unroll
  for (int k = 0; k < NK; k++) ldsm4t(a[k], a0 + k * 2048);
}
__device__ __forceinline__ uint64_t desc2(uint32_t lo, uint32_t hi) { uint64_t d; asm("mov.b64 %0,{%1,%2};" : "=l"(d) : "r"(lo), "r"(hi)); return d; }
__host__ __device__ __forceinline__ constexpr uint64_t wdesc(int off) { return mkdesc(C::SB0 + off, 8192, 1024); }
__host__ __device__ __forceinline__ constexpr uint64_t rdesc(int k) { return mkdesc_ns(C::SB0 + C::OFF_R + k * 256, 128, 10240); }
__host__ __device__ __forceinline__ constexpr uint64_t tdesc(int k) { return mkdesc_ns(C::SB0 + C::slot_off(k >> 2) + (k & 3) * 256, 128, 1024); }
template <int N>
__device__ __forceinline__ void store_pair(const float (&d)[N], int j0, int j1, uint32_t a) {
  stsm4(a, pack_bf16(d[4 * j0], d[4 * j0 + 1]), pack_bf16(d[4 * j0 + 2], d[4 * j0 + 3]), pack_bf16(d[4 * j1], d[4 * j1 + 1]), pack_bf16(d[4 * j1 + 2], d[4 * j1 + 3]));
}
__device__ __forceinline__ uint32_t tile_lane(int tid) { return (((tid >> 4) & 6) + ((tid >> 3) & 1)) * 1280 + (tid & 7) * 16; }
__device__ __forceinline__ void load_chunk(const CUtensorMap& tmX, uint32_t sb, int b, int c, int off, int bar) {
  tma3d_mc(sb + off, &tmX, c * 256, 4 * b, 0, sb + bar);
}
__device__ __forceinline__ void arrive_all(uint32_t sb, int bar, int i) {
  asm volatile("{.reg .pred p; .reg .b32 a; setp.lt.u32 p,%1,3; @p mapa.shared::cluster.u32 a,%0,%1; @p mbarrier.arrive.shared::cluster.b64 _,[a];}"
               ::"r"(sb + bar), "r"(i) : "memory");
}
__device__ __forceinline__ void probe(const ChainArgs& a, uint32_t sb, int job, int tries, int cta, int unit, int warp) {
  uint8_t* p = job < 5 ? a.mbuf + ((1 << job) >> 1) * 8192 + cta * 32 + (warp & 4) : a.mail + (size_t)min(unit, NUNIT) * MAIL_UNIT + warp * 128;
  uint32_t best[2] = {SENT, SENT};
#pragma unroll 1
  for (int r = 0; r < 2 * tries; r++) {
    const uint32_t t0 = clk32();
    uint32_t v;
    asm volatile("atom.relaxed.gpu.global.exch.b32 %0,[%1],-1;" : "=r"(v) : "l"(p + (r & 1) * 4096) : "memory");
    uint32_t dt = t0 - 1;
    asm volatile("{.reg .b64 c; .reg .pred p; setp.eq.b32 p,%1,-1; @p mov.u64 c,%%clock64; @p cvt.u32.u64 %0,c;}" : "+r"(dt) : "r"(v) : "memory");
    dt -= t0;
    if (r & 1) best[1] = min(best[1], dt); else best[0] = min(best[0], dt);
  }
  asm volatile("red.shared.min.u32 [%0],%1; red.shared.min.u32 [%0+4],%2;" ::"r"(sb + C::OFF_SEL + job * 8), "r"(best[0]), "r"(best[1]) : "memory");
}
#define WPF 3
__device__ __forceinline__ void load_piece(const CUtensorMap& tmWq, const CUtensorMap& tmWk, const CUtensorMap& tmWv, uint32_t sb, int col, int i) {
  using namespace C;
  const uint32_t bar = sb + BAR_M + 8 * (i & 3);
  mbar_expect_tx(bar, 16384);
  if (i < 10) { tma2d(sb + STAGE_Q + i * 8192, &tmWq, col, i * 64, bar); tma2d(sb + STAGE_V + i * 8192, &tmWv, col, i * 64, bar); }
  else { tma2d(sb + OFF_WK + (i - 10) * 16384, &tmWk, col, (i - 10) * 128, bar); tma2d(sb + OFF_WK + (i - 10) * 16384 + 8192, &tmWk, col, (i - 10) * 128 + 64, bar); }
}
static void fill_descs(ChainArgs& a) {
  using namespace C;
  for (int k = 0; k < 40; k++) a.td[k] = tdesc(k);
  for (int k = 0; k < 40; k++) { a.rd[k] = rdesc(k); a.kd[k] = wdesc(OFF_WK + k * 2048); a.od[k] = wdesc(wo_off(k >> 2) + (k & 3) * 2048); }
  for (int k = 0; k < 4; k++) a.kd[40 + k] = wdesc(OFF_WXQ + k * 2048);
  for (int k = 0; k < 12; k++) a.gd[k] = mkdesc_ns(SB0 + OFF_OG + k * 512, 256, 128);
  for (int k = 0; k < 8; k++) {
    a.sd[2 * k] = mkdesc_ns(SB0 + OFF_QT + (k >> 1) * 2560 + (k & 1) * 256, 1280, 128);
    a.sd[2 * k + 1] = mkdesc_ns(SB0 + OFF_KT + (k >> 1) * 2560 + (k & 1) * 640, 1280, 128);
  }
  for (int k = 0; k < 5; k++) a.vd[k] = mkdesc_ns(SB0 + OFF_VT + k * 256, 128, 1280);
  const int grp[4] = {0, 9, 1, 5};
  for (int k = 0; k < 12; k++) a.pd[k] = mkdesc_ns(SB0 + OFF_P + grp[k / 3] * 768 + (k % 3) * 256, 128, 768);
}

#define NT1 8
#define B1T 2
#define RIDL 0
#define S9E 1
#define F2K 16
#define PVE 0
#define QGA 3
#define NOX 0
#define VD 0
#define TD(k) a.td[k]
#define RD(k) a.rd[k]
template <int N, typename F>
__device__ __forceinline__ void k_chunk(F mma, float (&d)[N], uint32_t alo, uint32_t blo, uint32_t bhi) {
  wg_fence();
#pragma unroll
  for (int k = 0; k < 4; k++) mma(d, desc2(alo + k * 128, (uint32_t)(wdesc(0) >> 32)), desc2(blo + k * 16, bhi), 1);
  wg_commit();
}

__device__ __forceinline__ uint32_t quad_max_h2(uint32_t m) {
  const uint32_t a = __shfl_xor_sync(0xffffffffu, m, 1), b = __shfl_xor_sync(0xffffffffu, m, 2), c = __shfl_xor_sync(0xffffffffu, m, 3);
  return max_h2(max_h2(m, a), max_h2(b, c));
}
__device__ __forceinline__ uint32_t diag_mask(int lane) {
  const int dg = (lane >> 2) - 2 * (lane & 3);
  return dg >= 1 ? 0u : dg == 0 ? 0xFC000000u : 0xFC00FC00u;
}
__device__ __forceinline__ float quad_sum(float m) {
  const float a = __shfl_xor_sync(0xffffffffu, m, 1), b = __shfl_xor_sync(0xffffffffu, m, 2), c = __shfl_xor_sync(0xffffffffu, m, 3);
  return (m + a) + (b + c);
}
__device__ __forceinline__ float rcp(float x) { float y; asm("rcp.approx.ftz.f32 %0,%1;" : "=f"(y) : "f"(x)); return y; }
__device__ __forceinline__ void p_store(uint32_t base, bool layer, int lane, uint32_t p0, uint32_t p1, uint32_t p2, uint32_t p3, uint32_t p4) {
  stsm4(base + (layer ? 128 : 0) + lane * 16, p0, p1, p2, p3);
  stsm2(base + ((lane & 8) ? (layer ? 0 : 640) : (layer ? 640 : 512)) + (lane & 7) * 16, p4, 0u);
}

__device__ __forceinline__ void chain_q(const CUtensorMap& tmWk, const CUtensorMap& tmWo, const CUtensorMap& tmX, const ChainArgs& a,
                                        const uint32_t sb, const int tid0, const int cta, const int rank, Counters* cnt) {
  using namespace C;
  asm volatile("setmaxnreg.inc.sync.aligned.u32 208;");
  int left = SPIN_BUDGET;
  uint32_t wf[39][4];
  cnt_wait_warp(&cnt[CN_Z][0][32], 96, left);
  __threadfence();
  fence_async_all();
  mbar_wait(sb + BAR_W1, 0, left);
  PTS(4);
  load_wfrags<39>(wf, sb + STAGE_Q, tid0 >> 5, tid0 & 31);
  cluster_sync_relaxed();
  PTS(5);
  const uint32_t qa = sb + OFF_QT + tile_lane(tid0) + ((tid0 & 16) ? 9 * 128 : 0);
  const int dq = (tid0 & 16) ? -128 : 128;
  const int warp = __shfl_sync(0xffffffffu, tid0 >> 5, 0);
  if (tid0 < 4) mbar_expect_tx(sb + BAR_F0 + 8 * tid0, tid0 == 3 ? 20480 : (3 + (tid0 >> 1)) * SLOT);
  if (tid0 == 0) {
    load_chunk(tmX, sb, 0, rank, slot_off(rank), BAR_F0);
    load_chunk(tmX, sb, 0, 3 + rank, slot_off(3 + rank), BAR_F1);
    mbar_expect_tx(sb + BAR_W2, 32768);
    for (int i = 6; i < 10; i++) tma2d(sb + OFF_WK + i * 8192, &tmWk, (cta / 3) * DH + rank * 64, i * 64, sb + BAR_W2);
    mbar_expect_tx(sb + BAR_W3, 6 * 8192);
    for (int u = 2; u < 8; u++) tma2d(sb + wo_off(u), &tmWo, wo_col(u, rank), wo_row(u, cta), sb + BAR_W3);
  }
  __syncwarp();

  for (int b = 0; b < NS; b++) {
    const int ph = b & 1;
    {
      float d[24];
      mbar_wait(sb + BAR_F0, ph, left);
      if (b > 0) bar_sync(NB_GO, 256);
      TSB(b, 16);
      wg_fence();
#pragma unroll
      for (int k = 0; k < 12; k++) wgmma_rs48(d, wf[k], TD(k), k);
      wg_commit();
      mbar_wait(sb + BAR_F1, ph, left);
      wg_fence();
#pragma unroll
      for (int k = 12; k < F2K; k++) wgmma_rs48(d, wf[k], TD(k), 1);
      wg_commit();
      wg_wait<1>();
      arrive_all(sb, BAR_RE, tid0 - 32);
      if (warp == 0) {
        mbar_wait(sb + BAR_VF, ph, left);
        if (elect()) {
          load_chunk(tmX, sb, b, 6 + rank, slot_off(6) + rank * SLOT, BAR_F2);
          if (rank == 0) load_chunk(tmX, sb, b, 9, slot_off(9), BAR_F2);
        }
        TS(b, 21);
      }
      wg_fence();
#pragma unroll
      for (int k = F2K; k < 24; k++) wgmma_rs48(d, wf[k], TD(k), 1);
      if (RIDL == 0 && warp == 0 && rank) {
        mbar_wait(sb + BAR_RE, ph, left);
        if (elect()) bulk_g2s_mc(sb + OFF_R + (1 + rank) * 10240, a.xn + (size_t)(4 * b + 3 + (rank - 1) * (256 - 4 * LAG)) * 10240, 10240, sb + BAR_RID);
      }
      mbar_wait(sb + BAR_F2, ph, left);
      if (RIDL == 1 && warp == 0 && rank) {
        mbar_wait(sb + BAR_RE, ph, left);
        if (elect()) bulk_g2s_mc(sb + OFF_R + (1 + rank) * 10240, a.xn + (size_t)(4 * b + 3 + (rank - 1) * (256 - 4 * LAG)) * 10240, 10240, sb + BAR_RID);
      }
      wg_fence();
#pragma unroll
      for (int k = 24; k < 39; k++) wgmma_rs48(d, wf[k], TD(k), 1);
      wgmma_ts48(d, a.kd[40], TD(39), 1);
      wg_commit();
      wg_wait<0>();
      TS(b, 17);
      bar_arrive(NB_BQ, 256);
      arrive_all(sb, BAR_XE, tid0 - 32);
      bar_sync(NB_BV, 256);
#pragma unroll
      for (int j = 0; j < 3; j++) store_pair(d, j, j + 3, qa + (4 - j) * dq);
    }
    {
      float d[16];
      bar_sync(NB_M2, 256);
      TSB(b, 18);
      wg_fence();
#pragma unroll
      for (int k = 0; k < 39; k++) wgmma_rs32(d, wf[k], RD(k), k);
      wgmma_ts32(d, a.kd[40], RD(39), 1);
      wg_commit();
      wg_wait<0>();
      TS(b, 19);
      store_pair(d, 0, 1, qa);
      store_pair(d, 2, 3, qa + dq);
      fence_async();
      bar_arrive(NB_QK, 384);
    }
    const int bn = b + 1;
    if (tid0 < 4) mbar_expect_tx(sb + BAR_F0 + 8 * tid0, tid0 == 3 ? 20480 : (3 + (tid0 >> 1)) * SLOT);
    {
      const int lane = fresh(tid0) & 31;
      const bool up = warp >= 2, outer = warp == 0 || warp == 3;
      const uint32_t xo = xl_off(warp), ob = sb + xo + lane * 16;
      const uint32_t dm = diag_mask(lane);
      if (warp == 0) {
        bar_sync(NB_S, 288);
        if (bn < NS && elect()) {
          mbar_expect_tx(sb + BAR_ROT, 16384);
          bulk_g2s(sb + wo_off(0), a.rot + (size_t)cta * 32768, 16384, sb + BAR_ROT);
        }
        __syncwarp();
      }
      bar_sync(NB_X + warp, 64);
      fence_async();
      if (elect()) {
        const uint32_t r1 = mapa(sb, (rank + 1) % 3), r2 = mapa(sb, (rank + 2) % 3), n = outer ? 640 : 1152;
        bulk_s2c(r1 + xo + 3584, sb + xo + 7168, n, r1 + BAR_X + 8 + 8 * warp);
        bulk_s2c(r2 + xo, sb + xo + 7168, n, r2 + BAR_X + 8 + 8 * warp);
      }
      __syncwarp();
      mbar_wait(sb + BAR_X + 8 + 8 * warp, ph, left);
      {
        float z[10];
        const uint4 s = lds128(ob + 7168), u = lds128(ob), v = lds128(ob + 3584);
        const uint32_t ts = lds32(ob + 7168 + 512 - lane * 12), tu = lds32(ob + 512 - lane * 12), tv = lds32(ob + 3584 + 512 - lane * 12);
        const uint32_t h[5] = {add_h2(add_h2(s.x, u.x), v.x), add_h2(add_h2(s.y, u.y), v.y), add_h2(add_h2(add_h2(s.z, outer ? 0u : dm), u.z), v.z),
                               add_h2(add_h2(s.w, u.w), v.w), add_h2(add_h2(add_h2(ts, dm), tu), tv)};
        const uint32_t ma = max_h2(max_h2(h[0], h[1]), h[2]), mb = max_h2(h[3], h[4]);
        uint32_t m = max_h2(__byte_perm(ma, mb, 0x5410), __byte_perm(ma, mb, 0x7632));
        if (outer) m = max_h2(m, __byte_perm(m, m, 0x1032));
        const float2 mf = unpack_h2(quad_max_h2(m));
        const float m0 = -SCL * mf.x, m1 = -SCL * mf.y;
#pragma unroll
        for (int j = 0; j < 5; j++) {
          const float2 f = unpack_h2(h[j]);
          z[2 * j] = ex2(fmaf(f.x, SCL, j < 3 ? m0 : m1)); z[2 * j + 1] = ex2(fmaf(f.y, SCL, j < 3 ? m0 : m1));
        }
        float s0 = ((z[0] + z[1]) + (z[2] + z[3])) + (z[4] + z[5]), s1 = (z[6] + z[7]) + (z[8] + z[9]);
        if (outer) s0 = s1 = s0 + s1;
        s0 += __shfl_xor_sync(0xffffffffu, s0, 1); s1 += __shfl_xor_sync(0xffffffffu, s1, 1);
        s0 = rcp(s0 + __shfl_xor_sync(0xffffffffu, s0, 2)); s1 = rcp(s1 + __shfl_xor_sync(0xffffffffu, s1, 2));
        const uint32_t p3 = pack_bf16(z[6] * s1, z[7] * s1), p4 = pack_bf16(z[8] * s1, z[9] * s1);
        p_store(sb + OFF_P + (2 * warp + (up ? 2 : 1)) * 768, up, lane, pack_bf16(z[0] * s0, z[1] * s0), pack_bf16(z[2] * s0, z[3] * s0), pack_bf16(z[4] * s0, z[5] * s0),
                outer ? p3 : 0u, outer ? p4 : 0u);
        if (!outer) p_store(sb + OFF_P + (up ? 4 * 768 : 5 * 768), !up, lane, p3, p4, 0u, 0u, 0u);
      }
      fence_async();
      bar_arrive(NB_V, 384);
      TS(b, 31);
    }
  }
  if (left <= 0) g_err = 1;
}

__device__ __forceinline__ void chain_v(const ChainArgs& a, const uint32_t sb, const int tid0, const int cta, const int rank, Counters* cnt) {
  using namespace C;
  asm volatile("setmaxnreg.inc.sync.aligned.u32 224;");
  int left = SPIN_BUDGET;
  uint32_t wf[37][4];
  __threadfence();
  fence_async_all();
  mbar_wait(sb + BAR_W1, 0, left);
  load_wfrags<37>(wf, sb + STAGE_V + 3 * 2048, tid0 >> 5, tid0 & 31);
  cluster_sync_relaxed();
  uint32_t mo = (24 * rank + (tid0 >> 4)) * MAIL_UNIT + (cta / 24) * 8192 + ((cta / 3) & 7) * 256 + (tid0 & 15) * 16;
  const int blk9 = cta / 24 + (cta % 24 < 16 ? 0 : 4);
  uint32_t mo9 = (72 + (tid0 >> 3)) * MAIL_UNIT + blk9 * 8192 + ((cta % 24) & 15) * 128 + (tid0 & 7) * 16;
  mbar_wait(sb + BAR_W2, 0, left);
  const uint32_t ka = sb + OFF_KT + tile_lane(tid0) + ((tid0 & 16) ? 640 : 0);
  const int warp = __shfl_sync(0xffffffffu, tid0 >> 5, 0);

  for (int b = 0; b < NS; b++) {
    const int ph = b & 1;
    {
      float dv[24], dk[24];
#define VK(K0, K1)                                                   \
  wg_fence();                                                        \
  _Pragma("unroll") for (int k = K0; k < K1; k++) {                  \
    if (k < 3) wgmma_ts48(dv, a.kd[41 + k], TD(k), k);               \
    else wgmma_rs48(dv, wf[k - 3], TD(k), 1);                        \
    wgmma_ts48(dk, a.kd[k], TD(k), k);                               \
  }                                                                  \
  wg_commit();
      mbar_wait(sb + BAR_F0, ph, left);
      TSB(b, 22);
      VK(0, 12)
      mbar_wait(sb + BAR_F1, ph, left);
      VK(12, 15)
      wg_wait<1>();
      arrive_all(sb, BAR_RE, tid0);
      VK(15, 24)
      TS(b, 23);
      mbar_wait(sb + BAR_F2, ph, left);
      VK(24, 27)
      wg_wait<1>();
      bar_arrive(NB_BV, 256);
      VK(27, 40)
#undef VK
      wg_wait<0>();
      TS(b, 24);
      arrive_all(sb, BAR_XE, tid0);
      bar_sync(NB_BQ, 256);
#pragma unroll
      for (int j = 0; j < 3; j++) { store_pair(dk, j, j + 3, ka + (1 + j) * 128); store_pair(dv, j, j + 3, ka + 10240 + (1 + j) * 128); }
    }
    const bool succ = b + 1 < NS;
    {
      float d[16] = {};
      bar_sync(NB_M, 256);
#pragma unroll 1
      for (int c = 0; c < a.ten; c++) k_chunk(wgmma_ts32, d, (uint32_t)wdesc(OFF_WK) + c * 512, (uint32_t)rdesc(0) + c * 64, (uint32_t)(rdesc(0) >> 32));
      wg_wait<0>();
      TS(b, 25);
      store_pair(d, 0, 1, ka);
      store_pair(d, 2, 3, ka + 4 * 128);
      fence_async();
      bar_arrive(NB_QK, 384);
      bar_sync(NB_S, 288);
      wg_fence();
#pragma unroll
      for (int k = 0; k < 40; k++) {
        if (k < 3) wgmma_ts32(d, a.kd[41 + k], RD(k), k);
        else wgmma_rs32(d, wf[k - 3], RD(k), 1);
      }
      wg_commit();
      wg_wait<0>();
      TS(b, 26);
      arrive_all(sb, BAR_OE, tid0 - 32);
      if (warp == 0 && succ && elect()) {
        mbar_expect_tx(sb + BAR_OG, 2048);
        mbar_expect_tx(sb + BAR_OG2, 16384 + 2048);
        bulk_g2s(sb + wo_off(8), a.rot + (size_t)cta * 32768 + 16384, 16384, sb + BAR_OG2);
      }
      __syncwarp();
      store_pair(d, 0, 1, ka + 10240);
      store_pair(d, 2, 3, ka + 10240 + 4 * 128);
      fence_async();
      if (!succ) { bar_arrive(NB_V, 384); break; }
      mbar_wait(sb + BAR_ROT, ph, left);
    if (b == 0) {
      const uint32_t *p = &cnt[CN_S][0][0] + (24 * rank + (tid0 >> 4)) * 32, *q = &cnt[CN_S][0][0] + (72 + (tid0 >> 3)) * 32;
      uint32_t v0, v1, v2, v3;
      do {
        v0 = ld_relaxed(p); v1 = ld_relaxed(p + 256); v2 = ld_relaxed(p + 512); v3 = ld_relaxed(q);
      } while (__any_sync(0xffffffffu, !(v0 & v1 & v2 & v3 & 256)) && (left -= 16) > 0);
      __threadfence();
      mo |= ((v0 >> (cta / 24)) & 1) * 0x1003;
      mo ^= ((v1 >> (cta / 24)) & 1) | (((v2 >> (cta / 24)) & 1) << 1);
      mo9 |= ((v3 >> blk9) & 1) << 12;
    }
    }
    bar_sync(NB_P, 192);
    TSB(b, 27);
    {
      float o0[4], o1[4];
      wg_fence();
#pragma unroll
      for (int q = 0; q < 3; q++) {
        wgmma_ss8(o0, a.vd[q], a.pd[q], q);
        wgmma_ss8(o1, a.vd[2 + q], a.pd[3 + q], q);
      }
      wg_commit();
      wg_wait<0>();
      TS(b, 6);
      stsm4(sb + OFF_OG + tid0 * 16, pack_bf16(o0[0], o0[1]), pack_bf16(o1[0], o1[1]), pack_bf16(o0[2], o0[3]), pack_bf16(o1[2], o1[3]));
      fence_async();
    }
    bar_sync(NB_O, 160);
    TSB(b, 7);
    {
      float acc[4][8];
      wg_fence();
#pragma unroll
      for (int kk = 0; kk < 4; kk++) wgmma_tt16(acc[3], a.od[kk], a.gd[kk], kk);
#pragma unroll
      for (int i = 0; i < 3; i++)
#pragma unroll
        for (int kk = 0; kk < 4; kk++) {
          wgmma_tt16(acc[i], a.od[4 + 4 * i + kk], a.gd[kk], kk);
          if (i != 1 && kk == 3) wg_commit();
        }
      wg_wait<1>();
      arrive_all(sb, BAR_RQ, tid0);
      uint8_t* mb = a.mail + ph * 2048;
      const uint32_t tag = (b >> 1) & 1, radd = tag ? 0u : 0x10000u;
#define TAGPACK(LO, HI) (__byte_perm(((__float_as_uint(LO) + radd) & 0xFFFE0000u) | (tag << 16), pack_bf16(0.f, HI), 0x7632))
#define SEND(O, I) st_msg16(mb + (O), TAGPACK(acc[I][0], acc[I][2]), pack_bf16(acc[I][1], acc[I][3]), \
                            pack_bf16(acc[I][4], acc[I][6]), pack_bf16(acc[I][5], acc[I][7]))
      if (S9E == 1) { SEND(mo9, 3); __syncwarp(); }
      mbar_wait(sb + BAR_OG, ph, left);
      if (S9E == 2) { SEND(mo9, 3); __syncwarp(); }
      TS(b, 8);
      wg_fence();
#pragma unroll
      for (int k = 0; k < 12; k++) wgmma_tt16(acc[k >> 2], a.od[16 + k], a.gd[4 + (k & 3)], 1);
      mbar_wait(sb + BAR_OG2, ph, left);
      TS(b, 29);
      wg_fence();
#pragma unroll
      for (int k = 0; k < 12; k++) {
        wgmma_tt16(acc[k >> 2], a.od[28 + k], a.gd[8 + (k & 3)], 1);
        if ((k & 3) == 3) wg_commit();
      }
      const uint32_t o = mo & ~3u;
      if (!S9E) { SEND(mo9, 3); __syncwarp(); }
      wg_wait<2>();
      SEND(o, 0);
      __syncwarp();
      wg_wait<1>();
      SEND((o ^ ((mo & 1) << 12)) + 8 * MAIL_UNIT, 1);
      __syncwarp();
      if (QGA == 2) bar_arrive(NB_GO, 256);
      wg_wait<0>();
      if (QGA == 3) bar_arrive(NB_GO, 256);
      TS(b, 30);
      if (PVE) bar_arrive(NB_V, 384);
      SEND((o ^ ((mo & 2) << 11)) + 16 * MAIL_UNIT, 2);
      if (!PVE) bar_arrive(NB_V, 384);
      if (QGA == 0) bar_arrive(NB_GO, 256);
#undef SEND
#undef TAGPACK
      TS(b, 9);
      arrive_all(sb, BAR_RF, tid0 - 96);
      if (VD) { const uint32_t t0 = clk32(); while (clk32() - t0 < VD) {} }
    }
  }
  if (left <= 0) g_err = 2;
}

__device__ __forceinline__ void sum_msg(float (&e)[8], const uint4& a, const uint4& b, const uint4& c, const uint4& d) {
  e[0] = (bf_lo(a.x) + bf_lo(b.x)) + (bf_lo(c.x) + bf_lo(d.x)); e[1] = (bf_hi(a.x) + bf_hi(b.x)) + (bf_hi(c.x) + bf_hi(d.x));
  e[2] = (bf_lo(a.y) + bf_lo(b.y)) + (bf_lo(c.y) + bf_lo(d.y)); e[3] = (bf_hi(a.y) + bf_hi(b.y)) + (bf_hi(c.y) + bf_hi(d.y));
  e[4] = (bf_lo(a.z) + bf_lo(b.z)) + (bf_lo(c.z) + bf_lo(d.z)); e[5] = (bf_hi(a.z) + bf_hi(b.z)) + (bf_hi(c.z) + bf_hi(d.z));
  e[6] = (bf_lo(a.w) + bf_lo(b.w)) + (bf_lo(c.w) + bf_lo(d.w)); e[7] = (bf_hi(a.w) + bf_hi(b.w)) + (bf_hi(c.w) + bf_hi(d.w));
}
__device__ __forceinline__ void publish(const ChainArgs& a, int b, int warp, uint32_t src, uint32_t o) {
  const uint32_t off = (o >> 12) * 8192 + (o & 4095);
  uint32_t v = SENT;
  if (warp < 2) {
    const uint2 p = lds64(src), q = lds64(src + 256), r = lds64(src + 512), s = lds64(src + 768);
    v = pack_bf16((__uint_as_float(p.x) + __uint_as_float(q.x)) + (__uint_as_float(r.x) + __uint_as_float(s.x)),
                  (__uint_as_float(p.y) + __uint_as_float(q.y)) + (__uint_as_float(r.y) + __uint_as_float(s.y)));
    if (b + 1 == LAG && o >= 10240) v = ld_relaxed(a.mbuf + 2 * 40960 + off);
  }
  uint8_t* dst = a.mbuf + (((b + 1 + (warp >> 1)) & 1) * 40960 + off);
  st_relaxed(dst, v);
  st_relaxed(dst + 4096, v);
}

__device__ __forceinline__ void store_o(const ChainArgs& a, const uint4 (&ok)[4], int b, int cta, int tid) {
  uint8_t* p = a.oimg + (uint32_t)(((b & 7) * 192 + cta) * 4096 + (tid >> 5) * 1024 + ((tid ^ ((tid >> 3) & 3)) & 31) * 16);
  *reinterpret_cast<uint4*>(p) = ok[0]; *reinterpret_cast<uint4*>(p + 512) = ok[1];
  *reinterpret_cast<uint4*>(p + 96 * 4096) = ok[2]; *reinterpret_cast<uint4*>(p + 96 * 4096 + 512) = ok[3];
}

__device__ __forceinline__ void fetch_rows(const ChainArgs& a, uint32_t sb, int warp, int slot, uint32_t al) {
  using namespace C;
  const uint8_t* src = a.mbuf + slot * 40960;
  mbar_expect_tx(sb + BAR_M + 8 * warp, 5120);
  bulk_g2s(sb + OFF_R + warp * 4096, src + (warp * 8192 + ((al >> warp) & 1) * 4096), 4096, sb + BAR_M + 8 * warp);
  bulk_g2s(sb + OFF_R + 16384 + warp * 1024, src + (32768 + (al & 16) * 256 + warp * 1024), 1024, sb + BAR_M + 8 * warp);
}

__device__ __forceinline__ void wo_permute(uint4& u, uint4& v) {
  const uint4 e = make_uint4(__byte_perm(u.x, u.y, 0x5410), __byte_perm(u.z, u.w, 0x5410), __byte_perm(v.x, v.y, 0x5410), __byte_perm(v.z, v.w, 0x5410));
  v = make_uint4(__byte_perm(u.x, u.y, 0x7632), __byte_perm(u.z, u.w, 0x7632), __byte_perm(v.x, v.y, 0x7632), __byte_perm(v.z, v.w, 0x7632));
  u = e;
}

__device__ __forceinline__ void chain_a(const CUtensorMap& tmWq, const CUtensorMap& tmWk, const CUtensorMap& tmWv, const CUtensorMap& tmWo, const CUtensorMap& tmX,
                                        const ChainArgs& a, const uint32_t sb, const int tid0, const int cta, const int rank, const int unit, Counters* cnt) {
  using namespace C;
  asm volatile("setmaxnreg.dec.sync.aligned.u32 72;");
  int left = SPIN_BUDGET;
  const int warp = __shfl_sync(0xffffffffu, tid0 >> 5, 0);
  if (warp == 0) {
    const int col = (cta / 3) * DH + rank * 64;
#pragma unroll 1
    for (int i = 0; i < 16; i++) {
      if (i < 13) mbar_wait(sb + BAR_M + 8 * (i & 3), (i >> 2) & 1, left);
      if (tid0 == 0) {
        if (i == 9) mbar_arrive(sb + BAR_W1);
        if (i >= 13) mbar_arrive(sb + BAR_M + 8 * (i & 3));
        else if (i + WPF < 13) load_piece(tmWq, tmWk, tmWv, sb, col, i + WPF);
        else if (i + WPF < 15) { tma2d_prefetch(&tmWk, col, (i + WPF - 10) * 128); tma2d_prefetch(&tmWk, col, (i + WPF - 10) * 128 + 64); }
        else if (i + WPF == 15) for (int u = 2; u < 8; u++) tma2d_prefetch(&tmWo, wo_col(u, rank), wo_row(u, cta));
      }
      __syncwarp();
    }
  } else {
    if ((tid0 & 31) == 0) probe(a, sb, warp == 3 ? 5 : warp - 1, NT1, cta, unit, warp);
    __syncwarp();
    cnt_wait_warp(&cnt[CN_Z][0][32], 96, left);
  }
  PT2(3, 0); PT2(4, 32);
  bar_sync(NB_V, 384);
  uint32_t rsel;
  {
    const int lane = tid0 & 31;
    const uint2 t = lds64(sb + OFF_SEL + min(lane, 5) * 8);
    const uint32_t near = __ballot_sync(0xffffffffu, t.y < t.x), flip = ((near >> 1) ^ ((near & 1) * 15)) & 15;
    rsel = __ballot_sync(0xffffffffu, lane < 10 ? PL2 && ((near ^ __popc(lane & flip)) & 1) : PL1 && (((near >> 5) ^ __popc((lane - 10) & flip)) & 1)) & 0x3ffff;
  }
  cluster_sync_relaxed();
  arrive_all(sb, BAR_RF, tid0);
  arrive_all(sb, BAR_VF, tid0);
  fence_async_all();
  if (elect()) fetch_rows(a, sb, warp, 2, 0);
  __syncwarp();
  if (unit < NUNIT) {
#pragma unroll 1
    for (int i = tid0; i < (unit < 72 ? 1024 : 2048); i += 128)
      *reinterpret_cast<uint4*>(a.mail + (size_t)unit * MAIL_UNIT + (i >> 8) * 8192 + ((rsel >> (10 + (i >> 8))) & 1) * 4096 + (i & 255) * 16) = make_uint4(SENT, SENT, SENT, SENT);
  }
  bar_sync(NB_MR, 128);
  if (tid0 == 96) asm volatile("st.release.gpu.global.b32 [%0],%1;" ::"l"(&cnt[CN_S][0][0] + unit * 32), "r"(256 | (rsel >> 10)) : "memory");
  __syncwarp();
  mbar_wait(sb + BAR_RID, 0, left);
  mbar_wait(sb + BAR_M + 8 * warp, 0, left);
  bar_arrive(NB_M, 256);
  bar_arrive(NB_M2, 256);
  TS(0, 0);
  mbar_wait(sb + BAR_W3, 0, left);
  PTS(6);
#pragma unroll 4
  for (int it = tid0; it < 1536; it += 128) {
    const int row = it >> 2, q = it & 3;
    const uint32_t a0 = sb + OFF_WO + row * 128 + (((2 * q) ^ (row & 7)) << 4), a1 = a0 ^ 16;
    uint4 u = lds128(a0), v = lds128(a1);
    wo_permute(u, v);
    sts128(a0, u);
    sts128(a1, v);
  }
  fence_async();
  uint32_t mph = 1;
  uint32_t mo = (unit < NUNIT ? unit : NUNIT) * MAIL_UNIT + warp * 8192 + ((rsel >> (10 + warp)) & 1) * 4096 + (tid0 & 31) * 16;
  const uint32_t mo2 = 32768 + (((rsel >> (10 + warp)) ^ (rsel >> (14 + warp))) & 1) * 4096;
  DUR(1);
  __syncwarp();

  for (int b = 0; b < NS; b++) {
    const int ph = b & 1;
    if (tid0 < 5) mbar_expect_tx(sb + BAR_X + 8 * tid0, tid0 == 0 ? 2560 : (tid0 & 2) ? 2304 : 1280);
    if ((tid0 & 31) == 8) mbar_expect_tx(sb + BAR_M + 8 * warp, 5120);
    TS_FLUSH(b - 1);
    mbar_wait(sb + BAR_XE, ph, left);
    {
      const int lane = fresh(tid0) & 31, w = fresh(warp);
      const bool up = w >= 2, outer = w == 0 || w == 3;
      const uint32_t r1 = mapa(sb, (rank + 1) % 3), r2 = mapa(sb, (rank + 2) % 3);
      const uint32_t pa = OFF_P + (2 * w + (up ? 3 : 0)) * 768;
      const uint32_t ob = xl_off(w) + lane * 16;
      const uint32_t oa = outer ? pa + lane * 16 : ob + 640, oc = outer ? OFF_XM + (up ? 640 : 0) + lane * 16 : ob + 640 + 3584;
      float x0[20], x1[20];
      bar_sync(NB_QK, 384);
      TSB(b, 1);
      wg_fence();
#pragma unroll
      for (int kk = 0; kk < 4; kk++) {
        wgmma_tt40(x0, a.sd[4 * kk], a.sd[4 * kk + 1], kk);
        wgmma_tt40(x1, a.sd[4 * kk + 2], a.sd[4 * kk + 3], kk);
      }
      wg_commit();
      wg_wait<0>();
      bar_arrive(NB_S, 288);
      TS(b, 2);
      uint32_t h[5], z[5];
#pragma unroll
      for (int j = 0; j < 5; j++) h[j] = pack_h2(up ? x1[4 * j + 2] : x0[4 * j], up ? x1[4 * j + 3] : x0[4 * j + 1]);
      if (outer) {
        st_async4(r1 + oc, h[0], h[1], h[2], h[3], r1 + BAR_X);
        st_async4(r2 + oa, h[0], h[1], h[2], h[3], r2 + BAR_X);
        st_async1(r1 + oc + 512 - lane * 12, h[4], r1 + BAR_X);
        st_async1(r2 + oa + 512 - lane * 12, h[4], r2 + BAR_X);
      } else {
        sts128(sb + oa + 7168, make_uint4(h[0], h[1], h[2], h[3]));
      }
#pragma unroll
      for (int j = 0; j < 5; j++) z[j] = pack_h2(up ? x1[4 * j] : x0[4 * j + 2], up ? x1[4 * j + 1] : x0[4 * j + 3]);
      if (!outer) {
#pragma unroll
        for (int j = 0; j < 2; j++) z[3 + j] = pack_h2(up ? x0[4 * j] : x1[4 * j + 2], up ? x0[4 * j + 1] : x1[4 * j + 3]);
        h[3] = add_h2(h[3], diag_mask(lane));
      }
      sts128(sb + ob + 7168, make_uint4(z[0], z[1], z[2], z[3]));
      sts32(sb + ob + 7168 + 512 - lane * 12, z[4]);
      bar_arrive(NB_X + w, 64);
      TS(b, 3);
      mbar_wait(sb + BAR_X + (outer ? 0 : 8 + 8 * w), ph, left);
      TS(b, 4);
      {
        const uint4 u = lds128(sb + oa), v = lds128(sb + oc);
        const uint32_t tu = lds32(sb + oa + 512 - lane * 12), tv = lds32(sb + oc + 512 - lane * 12);
        h[0] = add_h2(add_h2(h[0], u.x), v.x); h[1] = add_h2(add_h2(h[1], u.y), v.y); h[2] = add_h2(add_h2(h[2], u.z), v.z);
        h[3] = add_h2(add_h2(h[3], u.w), v.w); h[4] = outer ? add_h2(add_h2(h[4], tu), tv) : 0xFC00FC00u;
        const float2 mf = unpack_h2(quad_max_h2(max_h2(max_h2(max_h2(h[0], h[1]), max_h2(h[2], h[3])), h[4])));
        const float m = -SCL * fmaxf(mf.x, mf.y);
        float y[10];
#pragma unroll
        for (int j = 0; j < 5; j++) { const float2 f = unpack_h2(h[j]); y[2 * j] = ex2(fmaf(f.x, SCL, m)); y[2 * j + 1] = ex2(fmaf(f.y, SCL, m)); }
        const float r = rcp(quad_sum(((y[0] + y[1]) + (y[2] + y[3])) + ((y[4] + y[5]) + (y[6] + y[7])) + (y[8] + y[9])));
        p_store(sb + pa, up, lane, pack_bf16(y[0] * r, y[1] * r), pack_bf16(y[2] * r, y[3] * r), pack_bf16(y[4] * r, y[5] * r),
                pack_bf16(y[6] * r, y[7] * r), pack_bf16(y[8] * r, y[9] * r));
      }
      fence_async();
      if (outer) bar_arrive(NB_P, 192);
      TS(b, 5);
    }
    const int bn = b + 1;
    if (warp == 0 && bn < NS) {
      if (!NOX && bn >= LAG) {
        cnt_wait_warp(&cnt[CN_X][bn - LAG][0], 4, left);
        fence_async_all();
      }
      mbar_wait(sb + BAR_OE, ph, left);
      if (elect()) load_chunk(tmX, sb, bn, rank, slot_off(0) + rank * SLOT, BAR_F0);
      TS(b, 20);
      mbar_wait(sb + BAR_RQ, ph, left);
      if (elect()) load_chunk(tmX, sb, bn, 3 + rank, slot_off(3) + rank * SLOT, BAR_F1);
      __syncwarp();
    }
    if (warp == 3 && bn < NS) {
      const uint32_t r1 = mapa(sb, (rank + 1) % 3), r2 = mapa(sb, (rank + 2) % 3);
      mbar_wait(sb + BAR_OE, ph, left);
      bar_sync(NB_O, 160);
      if (elect()) {
        bulk_s2c(r1 + OFF_OG + 2048, sb + OFF_OG, 2048, r1 + BAR_OG);
        bulk_s2c(r2 + OFF_OG + 4096, sb + OFF_OG, 2048, r2 + BAR_OG2);
      }
      __syncwarp();
    }
    uint4 x[6], ok[4];
    bar_sync(NB_V, 384);
    {
      float o0[16], o1[16];
      wg_fence();
#pragma unroll
      for (int q = 0; q < 3; q++) {
        wgmma_ss32(o0, a.vd[q], a.pd[6 + q], q);
        wgmma_ss32(o1, a.vd[2 + q], a.pd[9 + q], q);
      }
      wg_commit();
      if (bn < NS) {
        if (unit < 72) mbar_wait(sb + BAR_RF, ph ^ 1, left);
        if (QGA == 1) bar_arrive(NB_GO, 256);
        if (B1 && unit < 72 && (unit >> 3) % 3 >= B1T) { const uint32_t t0 = clk32(); while (clk32() - t0 < B1) {} }
      }
      ld_msg16x4(x, a.mail + mo);
      __syncwarp();
      wg_wait<0>();
      arrive_all(sb, BAR_VF, tid0);
#pragma unroll
      for (int h = 0; h < 2; h++) {
        ok[h] = make_uint4(pack_bf16(o0[12 + 2 * h], o0[13 + 2 * h]), pack_bf16(o0[8 + 2 * h], o0[9 + 2 * h]),
                           pack_bf16(o0[4 + 2 * h], o0[5 + 2 * h]), pack_bf16(o0[2 * h], o0[1 + 2 * h]));
        ok[2 + h] = make_uint4(pack_bf16(o1[2 * h], o1[1 + 2 * h]), pack_bf16(o1[4 + 2 * h], o1[5 + 2 * h]),
                               pack_bf16(o1[8 + 2 * h], o1[9 + 2 * h]), pack_bf16(o1[12 + 2 * h], o1[13 + 2 * h]));
      }
      TS(b, 28);
    }
    if (bn < NS) {
      const int lane = fresh(tid0) & 31;
      const uint32_t tag = (b >> 1) & 1;
      int n = 1;
      float e[8];
      if (unit < 72) {
#pragma unroll 1
        while (true) {
          const bool bad = __any_sync(0xffffffffu, differ4(x[0].x, x[1].x, x[2].x, x[3].x, tag) & 1);
          sum_msg(e, x[0], x[1], x[2], x[3]);
          if (!bad || (left -= 16) <= 0) break;
          ld_msg16x4(x, a.mail + mo);
          n++;
        }
        TS(b, 10);
        TSV(b, 15, n);
        float f[4];
        const bool b4 = lane & 16;
#pragma unroll
        for (int i = 0; i < 4; i++) f[i] = (b4 ? e[4 + i] : e[i]) + __shfl_xor_sync(0xffffffffu, b4 ? e[i] : e[4 + i], 16);
        sts128(sb + OFF_SCR + (lane & 16) * 64 + warp * 256 + (lane & 15) * 16, make_uint4(__float_as_uint(f[0]), __float_as_uint(f[1]), __float_as_uint(f[2]), __float_as_uint(f[3])));
        bar_sync(NB_MR, 128);
        publish(a, b, warp, sb + OFF_SCR + warp * 1024 + (lane & 3) * 64 + (lane >> 2) * 8, (warp & 1) * 10240 + unit * 128 + lane * 4);
      } else if (unit < NUNIT) {
        ld_msg16x2(x + 4, a.mail + (mo ^ mo2));
        __syncwarp();
#pragma unroll 1
        while (true) {
          const bool bad = __any_sync(0xffffffffu, (differ4(x[0].x, x[1].x, x[2].x, x[3].x, tag) | differ4(x[4].x, x[5].x, x[4].x, x[5].x, tag)) & 1);
          sum_msg(e, x[0], x[1], x[2], x[3]);
          e[0] += bf_lo(x[4].x) + bf_lo(x[5].x); e[1] += bf_hi(x[4].x) + bf_hi(x[5].x); e[2] += bf_lo(x[4].y) + bf_lo(x[5].y); e[3] += bf_hi(x[4].y) + bf_hi(x[5].y);
          e[4] += bf_lo(x[4].z) + bf_lo(x[5].z); e[5] += bf_hi(x[4].z) + bf_hi(x[5].z); e[6] += bf_lo(x[4].w) + bf_lo(x[5].w); e[7] += bf_hi(x[4].w) + bf_hi(x[5].w);
          if (!bad || (left -= 16) <= 0) break;
          ld_msg16x6(x, a.mail + mo, a.mail + (mo ^ mo2));
          n++;
        }
        TS(b, 10);
        TSV(b, 15, n);
        float f[4];
        const bool b4 = lane & 16, b3 = lane & 8;
#pragma unroll
        for (int i = 0; i < 4; i++) f[i] = (b4 ? e[4 + i] : e[i]) + __shfl_xor_sync(0xffffffffu, b4 ? e[i] : e[4 + i], 16);
        const float h0 = (b3 ? f[2] : f[0]) + __shfl_xor_sync(0xffffffffu, b3 ? f[0] : f[2], 8);
        const float h1 = (b3 ? f[3] : f[1]) + __shfl_xor_sync(0xffffffffu, b3 ? f[1] : f[3], 8);
        asm volatile("st.shared.v2.f32 [%0],{%1,%2};" ::"r"(sb + OFF_SCR + warp * 256 + lane * 8), "f"(h0), "f"(h1) : "memory");
        bar_sync(NB_MR, 128);
        if (!(warp & 1))
          publish(a, b, warp, sb + OFF_SCR + lane * 8, (lane >> 4) * 10240 + (36 + (unit >> 1)) * 128 + (lane & 3) * 32 + (lane & 8) * 2 + (unit & 1) * 8 + (lane & 4));
      }
      const uint32_t t0 = clk32();
      mo ^= 2048;
      TS(b, 11);
      if (rank < 2) {
        const int q = 2 * rank + (warp >> 1), blk = (warp & 1) ? 4 : q, o = blk * 4096 + ((warp & 1) ? q * 1024 : 0);
        const uint8_t* src = a.mbuf + (uint32_t)((ph ^ 1) * 40960 + o + (blk + ((rsel >> (5 - 5 * ph + blk)) & 1)) * 4096);
        while (clk32() - t0 < B2) {}
        if (elect()) bulk_g2s_mc(sb + OFF_R + o, src, (warp & 1) ? 1024 : 4096, sb + BAR_M + 8 * q);
        __syncwarp();
      }
      TS(b + 1, 12);
    }
    if (OSP == 1) store_o(a, ok, b, cta, fresh(tid0));
    if (bn < NS) {
      const int lane = fresh(tid0) & 31;
      const uint32_t va = sb + OFF_R + lane * 32 + (lane & 28);
      int n = 0;
      mbar_wait(sb + BAR_RID, ph ^ 1, left);
#pragma unroll 1
      while (true) {
        mbar_wait(sb + BAR_M + 8 * warp, mph, left);
        if (n == 0) TS(bn, 13);
        const uint32_t v0 = lds32(va + warp * 4096), v1 = lds32(va + warp * 4096 + 1024), v2 = lds32(va + warp * 4096 + 2048), v3 = lds32(va + warp * 4096 + 3072);
        const uint32_t v4 = lds32(va + 16384 + warp * 1024), v5 = lds32((va ^ 8) + (warp == 2 ? 9216 : 16384 + warp * 1024));
        mph ^= 1;
        n++;
        if (!__any_sync(0xffffffffu, max(max(max(v0, v1), v2), max(max(v3, v4), v5)) == SENT) || (left -= 16) <= 0) break;
        if (elect()) fetch_rows(a, sb, warp, ph ^ 1, rsel >> (5 - 5 * ph));
        __syncwarp();
      }
      bar_arrive(NB_M, 256);
      bar_arrive(NB_M2, 256);
      TS(bn, 0);
      TSV(bn, 14, n);
    }
    if (OSP == 0) store_o(a, ok, b, cta, fresh(tid0));
    bar_sync(NB_MR, 128);
    if (warp == 1 && elect()) cnt_signal(&cnt[CN_O][b][(cta >> 4) * 32]);
    __syncwarp();
  }
  TS_FLUSH(NS - 1);
  if (left <= 0) g_err = 3;
}

#define XF 1
#define NT2 4
__global__ void __cluster_dims__(3, 1, 1) __launch_bounds__(384, 1)
k_chain(const __grid_constant__ CUtensorMap tmWq, const __grid_constant__ CUtensorMap tmWk, const __grid_constant__ CUtensorMap tmWv,
        const __grid_constant__ CUtensorMap tmWo, const __grid_constant__ CUtensorMap tmX, const __grid_constant__ ChainArgs args) {
  using namespace C;
  extern __shared__ __align__(1024) uint8_t smem[];
  const uint32_t sb = smem_u32(smem);
  const int tid = threadIdx.x;
  const int wg = __shfl_sync(0xffffffffu, tid >> 7, 0);
  const int cta = blockIdx.x, rank = cta % 3;
  DUR(0);
  asm volatile("griddepcontrol.launch_dependents;");
  if (tid == 0) {
    if ((sb & 0xFFFFFF) != SB0) g_err = 100;
    for (int i = 0; i < 3; i++) mbar_init(sb + BAR_F0 + 8 * i, 1);
    mbar_init(sb + BAR_W1, 1); mbar_init(sb + BAR_W2, 1); mbar_init(sb + BAR_W3, 1);
    for (int i = 0; i < 5; i++) mbar_init(sb + BAR_X + 8 * i, 1);
    mbar_init(sb + BAR_OG2, 1);
    mbar_init(sb + BAR_XE, 6); mbar_init(sb + BAR_OG, 1); mbar_init(sb + BAR_OE, 3);
    mbar_init(sb + BAR_ROT, 1); mbar_init(sb + BAR_RQ, 3); mbar_init(sb + BAR_VF, 3); mbar_init(sb + BAR_RF, 3); mbar_init(sb + BAR_RE, 6);
    mbar_init(sb + BAR_RID, 1);
    for (int i = 0; i < 4; i++) mbar_init(sb + BAR_M + 8 * i, 1);
    asm volatile("fence.mbarrier_init.release.cluster;" ::: "memory");
    fence_async();
    if (!XF) for (int i = 0; i < WPF; i++) load_piece(tmWq, tmWk, tmWv, sb, (cta / 3) * DH + rank * 64, i);
  }
  if (tid >= 32 && tid < 44) sts32(sb + OFF_SEL + (tid - 32) * 4, SENT);
  const uint32_t launch = ld_relaxed(&g_launch);
  const int unit = rank < 2 ? (cta / 3) * 2 + rank : 64 + cta / 3;
  if (wg) {
    const int warp = tid >> 5, lane = tid & 31;
    uint4 v[3][3], e[4], f[4];
#pragma unroll
    for (int i = 0; i < 3; i++) ln_row_load(args.x0, v[i], min(cta + 96 * i, 255) * 8 + warp - 4, lane);
#pragma unroll
    for (int i = 0; i < 4; i++) {
      const int u = i < 2 ? i : i + 6;
      const uint4* src = reinterpret_cast<const uint4*>(args.wo + (size_t)(wo_row(u, cta) + ((tid - 128) >> 2)) * DM + wo_col(u, rank) + (tid & 3) * 16);
      e[i] = ld_nc16(src); f[i] = ld_nc16(src + 1);
    }
    __syncthreads();
    if (tid < 128 + 80) {
      const int j = cta * 80 + tid - 128, i = j % 2560, p = ((i >> 9) * 256 + (i & 255)) % 640;
      reinterpret_cast<uint4*>(args.mbuf)[j] = j < 5120 ? make_uint4(SENT, SENT, SENT, SENT) : ld_nc16(args.mem0 + (p & 7) * DM + (p >> 3) * 8);
    }
#pragma unroll
    for (int i = 0; i < 3; i++) ln_row(v[i], lane);
    uint4* st = reinterpret_cast<uint4*>(smem + STAGE_X);
#pragma unroll
    for (int i = 0; i < 3; i++) {
      const int g = cta + 96 * i;
      if (g < 256) {
#pragma unroll
        for (int j = 0; j < 3; j++)
          if (j < 2 || lane < 16) st[(lane + 32 * j) * 8 + (((warp - 4) ^ lane) & 7)] = v[i][j];
        bar_sync(NB_BQ, 256);
        for (int j = tid - 128; j < 640; j += 256) reinterpret_cast<uint4*>(args.xn)[g * 640 + j] = st[(j & ~7) | ((j ^ (j >> 3)) & 7)];
        bar_sync(NB_BQ, 256);
      }
    }
    PT2(0, 128);
    if (warp == 11) {
      if (lane == 0) cnt_signal(&g_cnt[launch & 1][CN_Z][0][32]);
      if (cta * 32 + lane < 7 * (NS + 1) * 6) (&g_cnt[~launch & 1][0][0][0])[(cta * 32 + lane) * 32] = 0;
      static_assert(7 * (NS + 1) * 6 <= 96 * 32, "counters");
    } else if (lane == 0 && warp != 7) probe(args, sb, 2 + (warp & 3), NT2, cta, unit, warp);
    __syncwarp();
    PT2(1, 128);
    bar_arrive(NB_V, 384);
#pragma unroll
    for (int i = 0; i < 4; i++) {
      const int row = (tid - 128) >> 2;
      wo_permute(e[i], f[i]);
      const uint32_t o = i * 8192 + row * 128 + (((2 * (tid & 3)) ^ (row & 7)) << 4);
      *reinterpret_cast<uint4*>(args.rot + (size_t)cta * 32768 + o) = e[i];
      *reinterpret_cast<uint4*>(args.rot + (size_t)cta * 32768 + (o ^ 16)) = f[i];
    }
  } else {
    __syncthreads();
    if (XF && tid == 0) for (int i = 0; i < WPF; i++) load_piece(tmWq, tmWk, tmWv, sb, (cta / 3) * DH + rank * 64, i);
    __syncwarp();
  }
  Counters* cnt = g_cnt[__shfl_sync(0xffffffffu, launch & 1, 0)];

  const int tid0 = __shfl_sync(0xffffffffu, tid & 127, tid & 31);
  if (wg == 0) chain_a(tmWq, tmWk, tmWv, tmWo, tmX, args, sb, tid0, cta, rank, unit, cnt);
  else if (wg == 1) chain_q(tmWk, tmWo, tmX, args, sb, tid0, cta, rank, cnt);
  else chain_v(args, sb, tid0, cta, rank, cnt);
  DUR(2);
  cluster_sync();
}

#define WDL 1
#define PRE 0
#define HD 0
namespace W {
constexpr int NW = 36, NP = 30, OW0 = 31;
constexpr int QST = 7;
constexpr int OFF_WS = 0;
constexpr int OFF_WQ = 94208;
constexpr int OFF_G = 176128;
constexpr int OFF_GO = 8192;
constexpr int OFF_Q = OFF_G + 24576;
constexpr int PITCH = 144;
constexpr int OFF_STG = OFF_Q;
constexpr int OFF_HIST = OFF_Q + QST * 4096;
constexpr int OFF_ST = OFF_HIST + 2240;
constexpr int OFF_BAR = OFF_ST + 256;
constexpr int SMEM = OFF_BAR + 272;
constexpr int BAR_GF = OFF_BAR, BAR_GE = OFF_BAR + 64, BAR_QF = OFF_BAR + 128, BAR_QE = OFF_BAR + 184, BAR_W1 = OFF_BAR + 240, BAR_W2 = OFF_BAR + 248,
              BAR_H = OFF_BAR + 256;
constexpr int NB_PRO = 1, NB_Q = 2, NB_L = 3, NB_L2 = 4, NB_A = 5;
constexpr uint32_t sb = C::SB0;
static_assert(SMEM <= 232448, "shared memory");
template <bool IS_O> __host__ __device__ constexpr bool in_smem(int k) { return IS_O ? k == 39 : (k & 7) == 2 || (k & 7) == 4 || ((k & 7) == 7 && k != 63); }
template <bool IS_O> __host__ __device__ constexpr int smem_before(int k) { return IS_O ? 0 : 3 * (k >> 3) + ((k & 7) > 2) + ((k & 7) > 4); }
template <bool IS_O> __host__ __device__ constexpr int chunk_k(int c) { return IS_O ? 5 * c : c < 4 ? 6 * c : 4 + 5 * c; }
template <bool IS_O> __host__ __device__ constexpr int stage_off(int c) { return IS_O ? OFF_GO + c * 5120 : OFF_G + (c & 3) * 6144; }
}

struct WorkArgs {
  const bf16* x0;
  bf16* out;
  const bf16* wqkv;
  uint64_t pd[24], od[40], qd[14], qw[42];
};
static void fill_descs(WorkArgs& a) {
  using namespace W;
  for (int k = 0; k < 24; k++) a.pd[k] = mkdesc64(sb + OFF_G + k * 1024, 512, 512);
  for (int k = 0; k < 40; k++) a.qw[k] = mkdesc(sb + OFF_WQ + k * 2048, 8192, 1024);
  for (int k = 0; k < 40; k++) a.od[k] = mkdesc_ns(sb + OFF_GO + k * 1024, 512, 128);
  for (int k = 0; k < 14; k++) a.qd[k] = mkdesc64(sb + OFF_Q + (k >> 1) * 4096 + (k & 1) * 32, 16, 512);
}
__device__ __forceinline__ void pass_wait(uint32_t target, int& left) {
  uint32_t v;
  do {
    asm volatile("ld.acquire.cta.shared.u32 %0,[%1];" : "=r"(v) : "r"(W::sb + W::BAR_H) : "memory");
    if (!__any_sync(0xffffffffu, v < target)) break;
    __nanosleep(30);
  } while (--left > 0);
}
__device__ __forceinline__ const uint8_t* opaque(const uint8_t* p) {
  return reinterpret_cast<const uint8_t*>(__shfl_sync(0xffffffffu, reinterpret_cast<unsigned long long>(p), 0));
}
__device__ __forceinline__ uint4 ld_relaxed16(const void* p) {
  uint4 v; asm volatile("ld.relaxed.gpu.global.v4.u32 {%0,%1,%2,%3},[%4];" : "=r"(v.x), "=r"(v.y), "=r"(v.z), "=r"(v.w) : "l"(p) : "memory"); return v;
}
__device__ __forceinline__ uint4 ld_msg8x2(const void* p) {
  uint4 v;
  asm volatile("{.reg .b64 a,b; ld.relaxed.gpu.global.v2.b64 {a,b},[%4]; mov.b64 {%0,%1},a; mov.b64 {%2,%3},b;}" : "=r"(v.x), "=r"(v.y), "=r"(v.z), "=r"(v.w) : "l"(p) : "memory");
  return v;
}
__device__ __forceinline__ void st_msg8(void* p, uint32_t x, uint32_t y) {
  asm volatile("{.reg .b64 r; mov.b64 r,{%1,%2}; st.relaxed.gpu.global.b64 [%0],r;}" ::"l"(p), "r"(x), "r"(y) : "memory");
}
template <bool LATE>
__device__ __forceinline__ bool job_of(int n, int& l, int& s) {
  const int i = n >> 1, j = n & 1;
  l = j; s = i - j * (LAG + LATE);
  return s >= 0 && s < NSEG;
}

template <bool IS_O>
__device__ __forceinline__ void work_g_weights(const CUtensorMap& tm, int w, int warp, bool second) {
  using namespace W;
  constexpr int NK = IS_O ? 40 : 64;
  const int col = (IS_O ? w - OW0 : w % 5) * 128, row = IS_O ? 0 : (w / 5) * 1024;
  int ns = 0;
#pragma unroll 1
  for (int k = 0; k < NK; k++) {
    const bool s = in_smem<IS_O>(k);
    if (s == second && (k & 1) == (warp & 1)) {
      const int t = warp >> 1;
      tma2d(sb + (s ? OFF_WS + (t * (IS_O ? 1 : 23) + ns) * 2048 : (t * 41 + k - ns) * 2048), &tm, col + t * 64, row + k * 16, sb + (s ? BAR_W2 : BAR_W1));
    }
    ns += s;
  }
}

template <bool IS_O>
__device__ __forceinline__ void work_g_producer(int w, Counters* cnt) {
  using namespace W;
  constexpr int NC = IS_O ? 8 : 12;
  int left = SPIN_BUDGET;
  uint32_t ph = 1;
#pragma unroll 1
  for (int i = 0; i < NS + IS_O; i++) {
    if (NOX && !IS_O && i >= LAG - 1 && i - LAG + 1 < NSEG) cnt_wait_warp(&cnt[CN_X][i - LAG + 1][0], 4, left);
    if (!IS_O) {
      cnt_wait_warp(&cnt[CN_O][i][(w / 5) * 32], 16, left);
      if (w == WW) WTS(i, 0);
      fence_async_all();
    }
#pragma unroll 1
    for (int j = 0; j < 2; j++) {
      int l, s;
      if (!job_of<IS_O>(2 * i + j, l, s)) continue;
      if (IS_O) {
        cnt_wait_warp(&cnt[CN_A][s][l * 32], 32, left);
        if (w == 35 && (l == 0 || i >= NSEG)) WTS(i, 8);
        fence_async_all();
      }
      const uint8_t* src = opaque(IS_O ? g_ob[s & 7][l] : g_o[i & 7][l][(w / 5) * 16]);
#pragma unroll 1
      for (int r = 0; r < NC / 4; r++) {
        const int n = !IS_O && r == 0 ? 6144 : 5120, s0 = IS_O ? 4 * r : 0;
#pragma unroll
        for (int c = 0; c < 4; c++) {
          mbar_wait(sb + BAR_GE + 8 * (s0 + c), ph, left);
          if (elect()) {
            mbar_expect_tx(sb + BAR_GF + 8 * (s0 + c), n);
            bulk_g2s(sb + stage_off<IS_O>(c) + s0 * 5120, src, n, sb + BAR_GF + 8 * (s0 + c));
          }
          src += n;
        }
        if (!IS_O || r) ph ^= 1;
      }
    }
  }
}

__device__ __forceinline__ uint32_t add_bf2(uint32_t a, uint32_t b) { uint32_t r; asm("add.rn.bf16x2 %0,%1,%2;" : "=r"(r) : "r"(a), "r"(b)); return r; }
template <int N, int LOW>
__device__ __forceinline__ void merge_stats(float m0, float m1, float q0, float q1, float& m, float& q, int lane) {
  const bool up = lane & 16;
  m = up ? m1 : m0; q = up ? q1 : q0;
  float n = 0.5f * N;
#pragma unroll
  for (int o = 16; o >= LOW; o >>= 1) {
    const float mo = __shfl_xor_sync(0xffffffffu, o < 16 ? m : up ? m0 : m1, o), qo = __shfl_xor_sync(0xffffffffu, o < 16 ? q : up ? q0 : q1, o);
    const float d = mo - m;
    m = fmaf(0.5f, d, m); q = fmaf(n * d, d, q + qo);
    n *= 2.f;
  }
}
template <int LOW>
__device__ __forceinline__ void pair_stats(const uint32_t (&x)[20], float& m, float& q, int lane) {
  float m0 = 0.f, m1 = 0.f, q0 = 0.f, q1 = 0.f;
#pragma unroll
  for (int j = 0; j < 20; j++) {
    const float e = bf_lo(x[j]), f = bf_hi(x[j]);
    m0 += e; m1 += f; q0 = fmaf(e, e, q0); q1 = fmaf(f, f, q1);
  }
  merge_stats<20, LOW>(m0 * 0.05f, m1 * 0.05f, fmaxf(fmaf(m0 * -0.05f, m0, q0), 0.f), fmaxf(fmaf(m1 * -0.05f, m1, q1), 0.f), m, q, lane);
}
__device__ __forceinline__ void add_product(uint32_t (&r)[20], const uint4 (&x)[5]) {
#pragma unroll
  for (int n = 0; n < 20; n++) {
    const uint4& v = x[n >> 2];
    const float2 f = unpack_h2((n & 3) == 0 ? v.x : (n & 3) == 1 ? v.y : (n & 3) == 2 ? v.z : v.w);
    r[n] = add_bf2(r[n], pack_bf16(f.x, f.y));
  }
}
__device__ __forceinline__ void load20(uint32_t (&r)[20], const uint8_t* p, int stride) {
#pragma unroll
  for (int m = 0; m < 5; m++) { const uint4 u = ld_relaxed16(p + m * stride); r[4 * m] = u.x; r[4 * m + 1] = u.y; r[4 * m + 2] = u.z; r[4 * m + 3] = u.w; }
}
__device__ __forceinline__ void poll5(uint4 (&x)[5], const uint8_t* src, int stride, uint32_t tag, int& left) {
#pragma unroll 1
  while (true) {
#pragma unroll
    for (int j = 0; j < 5; j++) x[j] = ld_msg8x2(src + j * stride);
    __syncwarp();
    const uint32_t bad = differ4(x[0].x, x[0].z, x[1].x, x[1].z, tag) | differ4(x[2].x, x[2].z, x[3].x, x[3].z, tag) | differ4(x[4].x, x[4].z, x[4].x, x[4].z, tag);
    if (!__any_sync(0xffffffffu, bad & 1) || (left -= 16) <= 0) break;
  }
}
__device__ __forceinline__ uint32_t norm_lo(uint32_t a, uint32_t b, float q, float m) { return pack_bf16(fmaf(bf_lo(a), q, m), fmaf(bf_lo(b), q, m)); }
__device__ __forceinline__ uint32_t norm_hi(uint32_t a, uint32_t b, float q, float m) { return pack_bf16(fmaf(bf_hi(a), q, m), fmaf(bf_hi(b), q, m)); }
__device__ __forceinline__ float part_var(float mp, float q, float n, float m) { const float d = mp - m; return fmaf(n * d, d, q); }
#define F(x) __uint_as_float(x)

__device__ __forceinline__ void work_l(const WorkArgs& a, int lane0, int p, int mask, Counters* cnt) {
  using namespace W;
  int left = SPIN_BUDGET;
#pragma unroll 1
  for (int n = 0; n < 2 * NS; n++) {
    int l, s;
    if (!job_of<false>(n, l, s) || !((mask >> l) & 1)) continue;
    cnt_wait_warp(&cnt[CN_P][s][l * 32], NP, left);
    if (p == 5 && lane0 == 0 && (l == 0 || n >= 2 * NSEG - 1)) WTS((n + 1) >> 1, 14);
    int lane = fresh(lane0);
    uint32_t r[20];
    const uint32_t ao = (p & 3) * 10240 + (p >> 2) * 64 + (lane >> 2) * 256 + (lane & 3) * 16;
    {
      uint4 x[5];
      const uint8_t* acc = g_part[s % MD][l] + ao;
#pragma unroll
      for (int m = 0; m < 5; m++) x[m] = ld_relaxed16(acc + m * 2048);
      if (l) {
        load20(r, g_xs[1] + (uint32_t)((s * 4 + (p >> 2)) * 10240 + (p & 3) * 16 + lane * 64), 2048);
      } else {
        const uint2* q = reinterpret_cast<const uint2*>(a.x0) + (uint32_t)((s * 16 + p) * 320 + lane);
#pragma unroll
        for (int m = 0; m < 5; m++)
          asm volatile("ld.global.nc.v2.u32 {%0,%2},[%4]; ld.global.nc.v2.u32 {%1,%3},[%4+1280];"
                       : "=r"(r[4 * m]), "=r"(r[4 * m + 1]), "=r"(r[4 * m + 2]), "=r"(r[4 * m + 3]) : "l"(q + m * 32));
        __syncwarp();
#pragma unroll
        for (int j = 0; j < 20; j += 2) { const uint32_t u = r[j]; r[j] = __byte_perm(u, r[j + 1], 0x5410); r[j + 1] = __byte_perm(u, r[j + 1], 0x7632); }
      }
      __syncwarp();
      add_product(r, x);
    }
    __syncwarp();
    lane = fresh(lane0);
    uint8_t* acc = g_part[s % MD][l] + ao;
    uint8_t* xp = g_xs[2 * l] + (uint32_t)((s * 16 + p) * 2560 + lane * 16);
#pragma unroll
    for (int m = 0; m < 5; m++) {
      *reinterpret_cast<uint4*>(xp + m * 512) = make_uint4(r[4 * m], r[4 * m + 1], r[4 * m + 2], r[4 * m + 3]);
      *reinterpret_cast<uint4*>(acc + m * 2048) = make_uint4(0, 0, 0, 0);
    }
    float m, q;
    pair_stats<1>(r, m, q, lane);
    q = rsqrtf(q * (1.f / DM) + 1e-5f);
    m *= -q;
    const float q0 = __shfl_sync(0xffffffffu, q, 0), q1 = __shfl_sync(0xffffffffu, q, 16);
    const float m0 = __shfl_sync(0xffffffffu, m, 0), m1 = __shfl_sync(0xffffffffu, m, 16);
    uint8_t* img = g_xnb[((n + 1) >> 1) & 7] + (uint32_t)((lane >> 3) * 4096 + (l * 16 + p) * 128 + (((lane & 7) ^ ((p & 3) << 1)) << 3));
#pragma unroll
    for (int j = 0; j < 20; j += 4) {
      __syncwarp();
      *reinterpret_cast<uint2*>(img + j * 4096) = make_uint2(norm_lo(r[j], r[j + 1], q0, m0), norm_lo(r[j + 2], r[j + 3], q0, m0));
      *reinterpret_cast<uint2*>(img + j * 4096 + 64) = make_uint2(norm_hi(r[j], r[j + 1], q1, m1), norm_hi(r[j + 2], r[j + 3], q1, m1));
    }
    __syncwarp();
    if (p == 5 && lane == 0 && (l == 0 || n >= 2 * NSEG - 1)) WTS((n + 1) >> 1, 4);
    if (elect()) cnt_signal(&cnt[CN_L][(n + 1) >> 1][0]);
    __syncwarp();
  }
  if (left <= 0) g_err = 14;
}

template <bool IS_O>
__device__ __forceinline__ void work_g(const WorkArgs& a, int w, int tile, int tid0, Counters* cnt) {
  using namespace W;
  constexpr int NC = IS_O ? 8 : 12, NST = IS_O ? 8 : 4;
  int left = SPIN_BUDGET;
  uint32_t ph = 0;
  constexpr int NR = IS_O ? 39 : 41;
  uint32_t wf[NR][4];
  mbar_wait(sb + BAR_W1, 0, left);
  load_wfrags<NR>(wf, sb + tile * 41 * 2048, tid0 >> 5, tid0 & 31);
  bar_sync(NB_PRO, 512);
  mbar_wait(sb + BAR_W2, 0, left);
  cnt_wait_warp(&cnt[CN_Z][0][0], NW, left);
  const uint32_t wlo = (uint32_t)mkdesc(C::SB0 + OFF_WS, 8192, 1024) + tile * (IS_O ? 128 : 23 * 128);
  constexpr uint32_t WHI = (uint32_t)(mkdesc(0, 8192, 1024) >> 32);
  const int g = (tid0 & 31) >> 2, t = tid0 & 3;
  const int col = (IS_O ? w - OW0 : w % 5) * 128 + tile * 64 + (tid0 >> 5) * 16 + ((g & 1) ? g + 7 : g);
  const uint32_t mo = (col >> 4) * 256 + t * 64 + (col & 15) * 4, mo0 = IS_O ? (col >> 2) * 64 + t * 16 + (col & 3) * 4 : mo;
#pragma unroll 1
  for (int il = 0; il < 2 * (NS + 1); il++) {
    int l, s;
    if (!job_of<IS_O>(il, l, s)) continue;
    float d[16];
    bool ok = false;
#pragma unroll
    for (int c = 0; c < NC; c++) {
      if (!PRE || !ok) mbar_wait(sb + BAR_GF + 8 * (c % NST), ph ^ ((c / NST) & 1), left);
      if (PRE && c + 1 < NC) ok = mbar_test(sb + BAR_GF + 8 * ((c + 1) % NST), ph ^ (((c + 1) / NST) & 1));
      if (c == 0 && w == (IS_O ? 35 : WW) && tid0 == 0 && tile == 0 && l == 0) WTS(il >> 1, IS_O ? 9 : 1);
      wg_fence();
#pragma unroll
      for (int k = chunk_k<IS_O>(c); k < chunk_k<IS_O>(c + 1); k++) {
        const uint64_t db = IS_O ? a.od[k] : a.pd[(c & 3) * 6 + k - chunk_k<IS_O>(c)];
        if (in_smem<IS_O>(k)) {
          const uint64_t da = desc2(wlo + smem_before<IS_O>(k) * 128, WHI);
          if (IS_O) wgmma_ts32(d, da, db, 1); else wgmma_tt32(d, da, db, 1);
        } else {
          if (IS_O) wgmma_rs32(d, wf[k - smem_before<IS_O>(k)], db, k); else wgmma_rt32(d, wf[k - smem_before<IS_O>(k)], db, k);
        }
      }
      wg_commit();
      if (c > 0) {
        wg_wait<1>();
        if (tid0 == 0) mbar_arrive(sb + BAR_GE + 8 * ((c - 1) % NST));
      }
    }
    ph ^= 1;
    wg_wait<0>();
    if (tid0 == 0) mbar_arrive(sb + BAR_GE + 8 * (NST - 1));
    uint8_t* dst = (IS_O ? g_prod[s % MD][l] : g_part[s % MD][l]) + (l ? mo : mo0);
    const uint32_t tag = (s / MD) & 1;
#pragma unroll
    for (int j = 0; j < 4; j++) {
      const uint32_t w0 = pack_h2(d[4 * j], d[4 * j + 1]), w1 = pack_h2(d[4 * j + 2], d[4 * j + 3]);
      const uint32_t r = __shfl_xor_sync(0xffffffffu, (g & 1) ? w0 : w1, 4);
      if (IS_O) st_msg8(dst + j * 10240, (((g & 1) ? r : w0) & ~1u) | tag, (g & 1) ? w1 : r);
      else asm volatile("red.relaxed.gpu.global.add.noftz.v2.f16x2 [%0],{%1,%2};" ::"l"(dst + j * 10240), "r"((g & 1) ? r : w0), "r"((g & 1) ? w1 : r) : "memory");
    }
    __syncwarp();
    if ((tid0 & 31) == 0) asm volatile("red.release.cta.shared.add.u32 [%0],1;" ::"r"(sb + BAR_H) : "memory");
    if (w == (IS_O ? 35 : WW) && tid0 == 0 && tile == 0) WTS(il >> 1, (IS_O ? 10 : 2) + l);
  }
  if (left <= 0) g_err = 11;
}

__device__ __forceinline__ void work_q_producer(Counters* cnt) {
  using namespace W;
  int left = SPIN_BUDGET;
#pragma unroll 1
  for (int i = 0; i <= NS; i++) {
    const uint8_t* src = opaque(g_xnb[i & 7]);
    cnt_wait_warp(&cnt[CN_L][i][0], (i < NSEG ? 16 : 0) + (i > LAG ? 16 : 0), left);
    if ((int)blockIdx.x == WW) WTS(i, 5);
    fence_async_all();
#pragma unroll 1
    for (int r = 0; r < 3; r++, src += QST * 4096) {
#pragma unroll
      for (int c = 0; c < QST; c++) {
        if (c == QST - 1 && r == 2) break;
        mbar_wait(sb + BAR_QE + 8 * c, ((c < QST - 1 ? i + r : r) & 1) ^ 1, left);
        if (elect()) {
          mbar_expect_tx(sb + BAR_QF + 8 * c, 4096);
          bulk_g2s(sb + OFF_Q + c * 4096, src + c * 4096, 4096, sb + BAR_QF + 8 * c);
        }
      }
    }
  }
}

__device__ __forceinline__ void work_q(const WorkArgs& a, int w, int tid0) {
  using namespace W;
  int left = SPIN_BUDGET;
  const int warp = __shfl_sync(0xffffffffu, tid0 >> 5, 0);
#pragma unroll 1
  for (int i = 0; i <= NS; i++) {
    {
      if (warp == 3 && i + 6 < NSEG && (tid0 & 31) < 20) {
        const int j = tid0 & 31;
        prefetch_l2((j < 10 ? g_xn[0] : reinterpret_cast<const uint8_t*>(a.x0)) + (size_t)(i + 6) * 40960 + (w * 10 + j % 10) * 128);
      }
      __syncwarp();
    }
    {
      float d[32] = {};
#pragma unroll 1
      for (int r = 0; r < 3; r++) {
#pragma unroll
        for (int c = 0; c < QST; c++) {
          if (c == QST - 1 && r == 2) break;
          mbar_wait(sb + BAR_QF + 8 * c, (c < QST - 1 ? i + r : r) & 1, left);
          wg_fence();
#pragma unroll
          for (int k = 2 * c; k < 2 * c + 2; k++) wgmma_ts64(d, a.qw[14 * r + k], a.qd[k], 1);
          wg_commit();
          wg_wait<1>();
          if ((c ? r < 2 : r > 0) && tid0 == 0) mbar_arrive(sb + BAR_QE + 8 * ((c + QST - 1) % QST));
        }
      }
      wg_wait<0>();
      if (w == WW && tid0 == 0) WTS(i, 6);
      const int lane = fresh(tid0) & 31;
      const uint32_t o = sb + OFF_STG + ((lane >> 4) * 8 + (lane & 7)) * PITCH + warp * 32 + (lane & 8) * 2;
      bar_sync(NB_Q, 128);
#pragma unroll
      for (int j = 0; j < 4; j++)
        stsm4t(o + 16 * j * PITCH, pack_bf16(d[8 * j], d[8 * j + 1]), pack_bf16(d[8 * j + 2], d[8 * j + 3]), pack_bf16(d[8 * j + 4], d[8 * j + 5]),
               pack_bf16(d[8 * j + 6], d[8 * j + 7]));
      bar_sync(NB_Q, 128);
    }
#pragma unroll 1
    for (int j = 0; j < 2; j++) {
      int l, s;
      if (!job_of<true>(2 * i + j, l, s)) continue;
      const bool ts = w == WW && (l == 0 || i >= NSEG);
      {
        const int tid = fresh(tid0), tk = tid >> 2, h = tid & 3;
        const float scl = 0.22360679774997896f * 1.4426950408889634f;
        const uint32_t kn = sb + OFF_STG + (l * 32 + tk) * PITCH + 40, ko = sb + OFF_HIST + (l * 14 + 14 + tk) * 80;
        float sc[2];
        {
          float q[20];
#pragma unroll
          for (int j = 0; j < 5; j++) {
            const uint2 u = lds64(kn - 40 + j * 8);
            q[4 * j] = bf_lo(u.x); q[4 * j + 1] = bf_hi(u.x); q[4 * j + 2] = bf_lo(u.y); q[4 * j + 3] = bf_hi(u.y);
          }
#pragma unroll
          for (int e = 0; e < 2; e++) {
            const int d = 4 * h + 2 * e;
            const uint32_t kv = tk >= d ? kn - d * PITCH : ko - d * 80;
            float s0 = 0.f, s1 = 0.f;
#pragma unroll
            for (int n = 0; n < 5; n++) {
              const uint2 u = lds64(kv + n * 8);
              s0 = fmaf(q[4 * n], bf_lo(u.x), s0); s1 = fmaf(q[4 * n + 1], bf_hi(u.x), s1);
              s0 = fmaf(q[4 * n + 2], bf_lo(u.y), s0); s1 = fmaf(q[4 * n + 3], bf_hi(u.y), s1);
            }
            sc[e] = s * 32 + tk >= d ? (s0 + s1) * scl : -INFINITY;
          }
        }
        uint32_t v[8][3];
#pragma unroll
        for (int j = 0; j < 8; j++) {
          const uint32_t kv = (tk >= 2 * j ? kn - 2 * j * PITCH : ko - 2 * j * 80) + 40 + h * 4;
          v[j][0] = lds32(kv); v[j][1] = lds32(kv + 16); v[j][2] = lds32(kv + (h < 2 ? 32 : 0));
        }
        float mx = fmaxf(sc[0], sc[1]);
        mx = fmaxf(fmaxf(mx, __shfl_xor_sync(0xffffffffu, mx, 1)), fmaxf(__shfl_xor_sync(0xffffffffu, mx, 2), __shfl_xor_sync(0xffffffffu, mx, 3)));
        sc[0] = ex2(sc[0] - mx); sc[1] = ex2(sc[1] - mx);
        const float inv = rcp(quad_sum(sc[0] + sc[1]));
        const uint32_t pp = pack_bf16(sc[0] * inv, sc[1] * inv);
        float o[6] = {};
#pragma unroll
        for (int j = 0; j < 4; j++) {
          const uint32_t p = __shfl_sync(0xffffffffu, pp, j, 4);
#pragma unroll
          for (int n = 0; n < 3; n++) {
            o[2 * n] = fmaf(bf_lo(p), bf_lo(v[2 * j][n]), o[2 * n]); o[2 * n + 1] = fmaf(bf_lo(p), bf_hi(v[2 * j][n]), o[2 * n + 1]);
            o[2 * n] = fmaf(bf_hi(p), bf_lo(v[2 * j + 1][n]), o[2 * n]); o[2 * n + 1] = fmaf(bf_hi(p), bf_hi(v[2 * j + 1][n]), o[2 * n + 1]);
          }
        }
        const int c = w * 10 + h;
        uint8_t* img = g_ob[s & 7][l] + tk * 16 + (c >> 2) * 512 + (c & 3) * 4;
#pragma unroll
        for (int n = 0; n < 3; n++)
          if (n < 2 || h < 2) *reinterpret_cast<uint32_t*>(img + n * 512) = pack_bf16(o[2 * n], o[2 * n + 1]);
      }
      bar_sync(NB_A, 160);
      if (ts && tid0 == 0) WTS(i, 15);
      {
        const int tid = fresh(tid0), r = tid >> 3, c = tid & 7;
        if (r < 14 && c < 5) {
          const uint32_t p = sb + OFF_STG + (l * 32 + 18 + r) * PITCH + 40 + c * 16;
          const uint2 u = lds64(p), v = lds64(p + 8);
          sts128(sb + OFF_HIST + (l * 14 + r) * 80 + c * 16, make_uint4(u.x, u.y, v.x, v.y));
        }
        __syncwarp();
      }
    }
    fence_async();
    bar_sync(NB_Q, 128);
    if (tid0 < QST - 1) mbar_arrive(sb + BAR_QE + 8 * tid0);
    __syncwarp();
  }
  if (left <= 0) g_err = 12;
}

__device__ __forceinline__ void work_f(const WorkArgs& a, int w, int tid0, Counters* cnt) {
  using namespace W;
  int left = SPIN_BUDGET;
  uint32_t passes = 0;
  const int warp = __shfl_sync(0xffffffffu, tid0 >> 5, 0), grp = w - 32;
#pragma unroll 1
  for (int n = 0; n < 2 * (NS + 1); n++) {
    int l, s;
    if (!job_of<true>(n, l, s)) continue;
    const int lane = fresh(tid0) & 31;
    cnt_wait_warp(&cnt[CN_A][s][l * 32], 32, left);
    uint32_t r[20];
    uint4 x[5];
    const uint8_t* res = g_xs[2 * l] + (uint32_t)(s * 40960 + grp * 10240);
    const uint8_t* src = g_prod[s % MD][l] + grp * 10240;
    if (l) load20(r, res + (warp * 2560 + lane * 16), 512);
    else load20(r, res + ((lane & 3) * 2560 + warp * 640 + (lane >> 2) * 16), 128);
    pass_wait(passes += 8, left);
    if (HD) { const uint32_t t0 = clk32(); while (clk32() - t0 < HD) {} }
    if (l) poll5(x, src + (warp * 64 + (lane >> 2) * 256 + (lane & 3) * 16), 2048, (s / MD) & 1, left);
    else poll5(x, src + (warp * 2560 + lane * 16), 512, (s / MD) & 1, left);
    add_product(r, x);
    if (l == 0) {
      uint8_t* xp = g_xs[1] + (uint32_t)(s * 40960 + grp * 10240 + warp * 2560 + lane * 16);
#pragma unroll
      for (int j = 0; j < 5; j++) *reinterpret_cast<uint4*>(xp + j * 512) = make_uint4(r[4 * j], r[4 * j + 1], r[4 * j + 2], r[4 * j + 3]);
      float m, q;
      pair_stats<4>(r, m, q, lane);
      if (!(lane & 12)) asm volatile("st.shared.v2.f32 [%0],{%1,%2};" ::"r"(sb + OFF_ST + (lane & 3) * 64 + (lane & 16) * 2 + warp * 8), "f"(m), "f"(q) : "memory");
      const bool odd = lane & 4;
      const uint32_t keep = odd ? 0x7632 : 0x5410, give = odd ? 0x5410 : 0x7632;
#pragma unroll
      for (int j = 0; j < 20; j += 4) {
        const uint32_t k0 = __byte_perm(r[j], r[j + 1], keep), k1 = __byte_perm(r[j + 2], r[j + 3], keep);
        const uint32_t g0 = __shfl_xor_sync(0xffffffffu, __byte_perm(r[j], r[j + 1], give), 4), g1 = __shfl_xor_sync(0xffffffffu, __byte_perm(r[j + 2], r[j + 3], give), 4);
        r[j] = odd ? g0 : k0; r[j + 1] = odd ? g1 : k1; r[j + 2] = odd ? k0 : g0; r[j + 3] = odd ? k1 : g1;
      }
      bar_sync(NB_Q, 128);
      const uint32_t sa = sb + OFF_ST + (lane & 3) * 64 + (lane & 4) * 8;
      const uint4 e0 = lds128(sa), e1 = lds128(sa + 16);
      m = 0.25f * ((F(e0.x) + F(e0.z)) + (F(e1.x) + F(e1.z)));
      q = rsqrtf(((part_var(F(e0.x), F(e0.y), 160.f, m) + part_var(F(e0.z), F(e0.w), 160.f, m)) +
                  (part_var(F(e1.x), F(e1.y), 160.f, m) + part_var(F(e1.z), F(e1.w), 160.f, m))) * (1.f / DM) + 1e-5f);
      m *= -q;
      uint8_t* dst = g_xn[1] + (uint32_t)((s * 4 + grp) * 10240 + (warp * 20 + (lane >> 3)) * 128 + (lane & 3) * 32 + (lane & 4) * 4);
#define NRM(V) pack_bf16(fmaf(bf_lo(V), q, m), fmaf(bf_hi(V), q, m))
#pragma unroll
      for (int j = 0; j < 20; j += 4) *reinterpret_cast<uint4*>(dst + j * 128) = make_uint4(NRM(r[j]), NRM(r[j + 1]), NRM(r[j + 2]), NRM(r[j + 3]));
#undef NRM
      bar_sync(NB_Q, 128);
      if (warp == 0 && elect()) cnt_signal(&cnt[CN_X][s][0]);
      __syncwarp();
    } else {
      uint2* dst = reinterpret_cast<uint2*>(a.out) + (uint32_t)((s * 16 + grp * 4 + warp) * 320 + lane);
#pragma unroll
      for (int j = 0; j < 20; j += 4) {
        dst[j * 8] = make_uint2(__byte_perm(r[j], r[j + 1], 0x5410), __byte_perm(r[j + 2], r[j + 3], 0x5410));
        dst[160 + j * 8] = make_uint2(__byte_perm(r[j], r[j + 1], 0x7632), __byte_perm(r[j + 2], r[j + 3], 0x7632));
      }
    }
    if (w == 35 && tid0 == 0) WTS(n >> 1, 12 + l);
  }
  if (left <= 0) g_err = 13;
}
#undef F

__global__ void __launch_bounds__(512, 1)
k_work(const __grid_constant__ CUtensorMap tmWo, const __grid_constant__ CUtensorMap tmBo, const __grid_constant__ WorkArgs args) {
  using namespace W;
  extern __shared__ __align__(1024) uint8_t smem[];
  const int tid = threadIdx.x, w = blockIdx.x;
  const int wg = __shfl_sync(0xffffffffu, tid >> 7, 0);
  const int tid0 = __shfl_sync(0xffffffffu, tid & 127, tid & 31);
  if (tid == 0) {
    if (smem_u32(smem) != sb) g_err = 101;
    for (int i = 0; i < 8; i++) { mbar_init(sb + BAR_GF + 8 * i, 1); mbar_init(sb + BAR_GE + 8 * i, 2); }
    for (int i = 0; i < QST; i++) { mbar_init(sb + BAR_QF + 8 * i, 1); mbar_init(sb + BAR_QE + 8 * i, 1); }
    mbar_init(sb + BAR_W1, 1); mbar_init(sb + BAR_W2, 1); sts32(sb + BAR_H, 0); sts32(sb + BAR_H + 4, 0);
    asm volatile("fence.mbarrier_init.release.cluster;" ::: "memory");
    fence_async();
    mbar_expect_tx(sb + BAR_W1, (w < NP ? 82 : 78) * 2048);
    mbar_expect_tx(sb + BAR_W2, (w < NP ? 46 : 2) * 2048);
  }
  Counters* cnt = g_cnt[launch_parity()];
  if (WDL && wg == 3) {
    int left = SPIN_BUDGET;
    cnt_wait_warp(&cnt[CN_Z][0][32], 96, left);
  }
  __syncthreads();

  if (wg < 2 && w < NP) {
    asm volatile("setmaxnreg.inc.sync.aligned.u32 208;");
    work_g<false>(args, w, wg, tid0, cnt);
  } else if (wg < 2) {
    asm volatile("setmaxnreg.inc.sync.aligned.u32 200;");
    if (w >= OW0) work_g<true>(args, w, wg, tid0, cnt);
    else {
      bar_sync(NB_PRO, 512);
      work_l(args, tid0 & 31, 12 + __shfl_sync(0xffffffffu, tid0 >> 5, 0), 1 << wg, cnt);
    }
  } else if (wg == 2 && w < 32) {
    asm volatile("setmaxnreg.dec.sync.aligned.u32 72;");
    for (int i = tid0; i < MD * 160; i += 128) reinterpret_cast<uint4*>(g_part[i / 160][w >> 4] + (w & 15) * 2560)[i % 160] = make_uint4(0, 0, 0, 0);
    bar_sync(NB_Q, 128);
    if (tid0 == 0) cnt_signal(&cnt[CN_Z][0][0]);
    for (int i = tid0; i < 560; i += 128) sts32(sb + OFF_HIST + i * 4, 0);
    bar_sync(NB_PRO, 512);
#pragma unroll 16
    for (int i = tid0; i < 640 * 32; i += 128) {
      const int k = i >> 5, c = i & 31;
      uint32_t v = 0;
      if (c < 30) v = *reinterpret_cast<const uint32_t*>(args.wqkv + (size_t)k * 1920 + (c / 10) * 640 + w * 20 + (c % 10) * 2);
      sts32(sb + OFF_WQ + (k >> 6) * 8192 + (k & 63) * 128 + (((c >> 2) ^ (k & 7)) << 4) + (c & 3) * 4, v);
    }
    fence_async();
    bar_sync(NB_Q, 128);
    work_q(args, w, tid0);
  } else if (wg == 2) {
    asm volatile("setmaxnreg.dec.sync.aligned.u32 56;");
    for (int i = tid0; i < MD * 1280; i += 128) reinterpret_cast<uint4*>(g_prod[i / 1280][(i / 640) & 1] + (w - 32) * (4 * 2560))[i % 640] = make_uint4(SENT, SENT, SENT, SENT);
    bar_sync(NB_Q, 128);
    if (tid0 == 0) cnt_signal(&cnt[CN_Z][0][0]);
    bar_sync(NB_PRO, 512);
    work_f(args, w, tid0, cnt);
  } else if (w >= 32) {
    asm volatile("setmaxnreg.dec.sync.aligned.u32 56;");
    const int warp = __shfl_sync(0xffffffffu, tid0 >> 5, 0);
    if (elect()) work_g_weights<true>(tmBo, w, warp, false);
    __syncwarp();
    bar_sync(NB_PRO, 512);
    if (elect()) work_g_weights<true>(tmBo, w, warp, true);
    __syncwarp();
    if (warp == 0) work_g_producer<true>(w, cnt);
    else work_l(args, tid0 & 31, (w - 32) * 3 + warp - 1, 3, cnt);
  } else {
    asm volatile("setmaxnreg.dec.sync.aligned.u32 24;");
    const int warp = __shfl_sync(0xffffffffu, tid0 >> 5, 0);
    if (elect()) {
      if (w < NP) work_g_weights<false>(tmWo, w, warp, false);
      else if (w >= OW0) work_g_weights<true>(tmBo, w, warp, false);
    }
    __syncwarp();
    bar_sync(NB_PRO, 512);
    if (elect()) {
      if (w < NP) work_g_weights<false>(tmWo, w, warp, true);
      else if (w >= OW0) work_g_weights<true>(tmBo, w, warp, true);
    }
    __syncwarp();
    if (warp == 0) {
      if (w < NP) work_g_producer<false>(w, cnt);
      else if (w >= OW0) work_g_producer<true>(w, cnt);
    } else if (warp == 1) {
      work_q_producer(cnt);
    } else if (warp == 2) {
      int left = SPIN_BUDGET;
      uint32_t passes = 0;
#pragma unroll 1
      for (int n = 0; n < 2 * NS; n++) {
        int l, s;
        if (w >= NP || !job_of<false>(n, l, s)) continue;
        pass_wait(passes += 8, left);
        if (elect()) cnt_signal(&cnt[CN_P][s][l * 32]);
        __syncwarp();
      }
    } else {
#pragma unroll 1
      for (int n = 0; n < 2 * (NS + 1); n++) {
        int l, s;
        if (!job_of<true>(n, l, s)) continue;
        bar_sync(NB_A, 160);
        if (elect()) cnt_signal(&cnt[CN_A][s][l * 32]);
        __syncwarp();
        if (w == WW && tid0 == 96 && (l == 0 || n >= 2 * NSEG)) WTS(n >> 1, 7);
      }
    }
  }
  asm volatile("griddepcontrol.wait;" ::: "memory");
  if (w == 35 && tid == 256) g_launch = ld_relaxed(&g_launch) + 1;
}

typedef CUresult (*EncodeFn)(CUtensorMap*, CUtensorMapDataType, cuuint32_t, void*, const cuuint64_t*, const cuuint64_t*,
                             const cuuint32_t*, const cuuint32_t*, CUtensorMapInterleave, CUtensorMapSwizzle,
                             CUtensorMapL2promotion, CUtensorMapFloatOOBfill);

static void make_map(EncodeFn enc, CUtensorMap* tm, const void* ptr, uint64_t cols, uint64_t rows, uint32_t boxc, uint32_t boxr,
                     CUtensorMapSwizzle sw = CU_TENSOR_MAP_SWIZZLE_128B, CUtensorMapL2promotion pr = CU_TENSOR_MAP_L2_PROMOTION_L2_256B) {
  cuuint64_t dims[2] = {cols, rows};
  cuuint64_t strides[1] = {cols * 2};
  cuuint32_t box[2] = {boxc, boxr};
  cuuint32_t es[2] = {1, 1};
  enc(tm, CU_TENSOR_MAP_DATA_TYPE_BFLOAT16, 2, const_cast<void*>(ptr), dims, strides, box, es, CU_TENSOR_MAP_INTERLEAVE_NONE,
      sw, pr, CU_TENSOR_MAP_FLOAT_OOB_FILL_NONE);
}

extern "C" void kernel_launch(void* const* d_in, const int* in_sizes, int n_in, void* d_out, int out_size) {
  const bf16* x0 = (const bf16*)d_in[0];
  const bf16* mem0 = (const bf16*)d_in[1];
  const bf16* Wq = (const bf16*)d_in[2];
  const bf16* Wk = (const bf16*)d_in[3];
  const bf16* Wv = (const bf16*)d_in[4];
  const bf16* Wo = (const bf16*)d_in[5];
  const bf16* Bqkv = (const bf16*)d_in[8];
  const bf16* Bwo = (const bf16*)d_in[9];
  bf16* out = (bf16*)d_out;

  static EncodeFn enc = nullptr;
  static uint8_t *p_xn, *p_o, *p_mbuf, *p_mail, *p_rot;
  if (!enc) {
    void* fn = nullptr;
    cudaDriverEntryPointQueryResult qr;
    cudaGetDriverEntryPoint("cuTensorMapEncodeTiled", &fn, cudaEnableDefault, &qr);
    enc = (EncodeFn)fn;
    cudaFuncSetAttribute(k_chain, cudaFuncAttributeMaxDynamicSharedMemorySize, C::SMEM);
    cudaFuncSetAttribute(k_work, cudaFuncAttributeMaxDynamicSharedMemorySize, W::SMEM);
    void* p;
    cudaGetSymbolAddress(&p, g_xn); p_xn = (uint8_t*)p;
    cudaGetSymbolAddress(&p, g_o); p_o = (uint8_t*)p;
    cudaGetSymbolAddress(&p, g_mbuf); p_mbuf = (uint8_t*)p;
    cudaGetSymbolAddress(&p, g_mail); p_mail = (uint8_t*)p;
    cudaGetSymbolAddress(&p, g_rot); p_rot = (uint8_t*)p;
  }
  CUtensorMap tmWq, tmWk, tmWv, tmWo, tmWo16, tmBo, tmX;
  make_map(enc, &tmWq, Wq, NH * DH, DM, 64, 64);
  make_map(enc, &tmWk, Wk, NH * DH, DM, 64, 64);
  make_map(enc, &tmWv, Wv, NH * DH, DM, 64, 64);
  make_map(enc, &tmWo, Wo, DM, NH * DH, 64, 64);
  make_map(enc, &tmWo16, Wo, DM, NH * DH, 64, 16);
  make_map(enc, &tmBo, Bwo, DM, DM, 64, 16);
  {
    cuuint64_t dims[3] = {2560, 4 * NS, 2};
    cuuint64_t strides[2] = {10240, (cuuint64_t)(256 - 4 * LAG) * 10240};
    cuuint32_t box[3] = {256, 3, 2};
    cuuint32_t es[3] = {1, 1, 1};
    enc(&tmX, CU_TENSOR_MAP_DATA_TYPE_UINT32, 3, p_xn, dims, strides, box, es, CU_TENSOR_MAP_INTERLEAVE_NONE,
        CU_TENSOR_MAP_SWIZZLE_NONE, CU_TENSOR_MAP_L2_PROMOTION_NONE, CU_TENSOR_MAP_FLOAT_OOB_FILL_NONE);
  }

  cudaStream_t st = cudaStreamPerThread;
  ChainArgs ca;
  ca.x0 = x0; ca.mem0 = mem0; ca.wo = Wo;
  ca.xn = p_xn;
  ca.oimg = p_o;
  ca.mbuf = p_mbuf; ca.mail = p_mail; ca.rot = p_rot;
  ca.ten = 10;
  fill_descs(ca);
  k_chain<<<96, 384, C::SMEM, st>>>(tmWq, tmWk, tmWv, tmWo, tmX, ca);
  WorkArgs wa;
  fill_descs(wa);
  wa.x0 = x0; wa.out = out;
  wa.wqkv = Bqkv;
  cudaLaunchAttribute at[1];
  at[0].id = cudaLaunchAttributeProgrammaticStreamSerialization; at[0].val.programmaticStreamSerializationAllowed = 1;
  cudaLaunchConfig_t cfg = {};
  cfg.gridDim = dim3(W::NW); cfg.blockDim = dim3(512); cfg.dynamicSmemBytes = W::SMEM; cfg.stream = st;
  cfg.attrs = at; cfg.numAttrs = 1;
  cudaLaunchKernelEx(&cfg, k_work, tmWo16, tmBo, wa);
}
```

```cpp
#include <cuda_runtime.h>
#include <cuda_bf16.h>
#include <cuda.h>
#include <stdint.h>

typedef __nv_bfloat16 bf16;

constexpr int SEQ = 2048, DM = 640, NH = 32, DH = 192, NSEG = 64;
#define LAG 6
constexpr int NS = NSEG + LAG;
constexpr uint32_t SENT = 0xFFFFFFFFu;
#define BUDGET_LOG 20
constexpr int SPIN_BUDGET = 1 << BUDGET_LOG;

constexpr int MD = 8;
static_assert(LAG <= 6, "depth of the rings");
constexpr int MAIL_UNIT = 65536, NUNIT = 88;
__device__ __align__(1024) uint8_t g_xn[2][32 * 10 * 8192];
__device__ __align__(1024) uint8_t g_xnb[8][81920];
__device__ __align__(1024) uint8_t g_ob[8][2][40960];
__device__ __align__(1024) uint8_t g_o[8][2][96][4096];
__device__ __align__(1024) uint8_t g_part[MD][2][16 * 2560];
__device__ __align__(1024) uint8_t g_prod[MD][2][16 * 2560];
__device__ __align__(131072) uint8_t g_mbuf[3][40960];
__device__ __align__(65536) uint8_t g_mail[NUNIT + 1][MAIL_UNIT];
__device__ __align__(1024) uint8_t g_rot[96][32768];
__device__ __align__(128) uint8_t g_xs[3][SEQ * DM * 2];
enum { CN_O = 0, CN_L = 1, CN_A = 2, CN_X = 3, CN_Z = 4, CN_P = 5, CN_S = 6 };
typedef uint32_t Counters[NS + 1][6 * 32];
__device__ __align__(128) Counters g_cnt[2][7];
__device__ uint32_t g_launch;
__device__ int g_err;
#define DUR(i)
#define TS(jj, i)
#define PTS(i)
#define PT2(i, t)
#define TSB(jj, i)
#define TSV(jj, i, v)
#define TS_FLUSH(jj)
#define WTS(i, k)
#define WW -1

__device__ __forceinline__ uint32_t smem_u32(const void* p) { return (uint32_t)__cvta_generic_to_shared(p); }
__device__ __forceinline__ uint32_t clk32() { unsigned long long t; asm volatile("mov.u64 %0, %%clock64;" : "=l"(t)::"memory"); return (uint32_t)t; }
__device__ __forceinline__ uint32_t mapa(uint32_t a, uint32_t r) { uint32_t o; asm("mapa.shared::cluster.u32 %0,%1,%2;" : "=r"(o) : "r"(a), "r"(r)); return o; }
__device__ __forceinline__ void mbar_init(uint32_t bar, uint32_t cnt) { asm volatile("mbarrier.init.shared::cta.b64 [%0],%1;" ::"r"(bar), "r"(cnt) : "memory"); }
__device__ __forceinline__ void mbar_expect_tx(uint32_t bar, uint32_t bytes) { asm volatile("mbarrier.arrive.expect_tx.shared::cta.b64 _,[%0],%1;" ::"r"(bar), "r"(bytes) : "memory"); }
__device__ __forceinline__ void mbar_arrive(uint32_t bar) { asm volatile("mbarrier.arrive.shared::cta.b64 _,[%0];" ::"r"(bar) : "memory"); }
__device__ __forceinline__ void mbar_arrive_cluster(uint32_t bar) { asm volatile("mbarrier.arrive.shared::cluster.b64 _,[%0];" ::"r"(bar) : "memory"); }
__device__ __forceinline__ bool mbar_try(uint32_t bar, uint32_t ph) {
  uint32_t ok;
  asm volatile("{.reg .pred p; mbarrier.try_wait.parity.shared::cta.b64 p,[%1],%2; selp.u32 %0,1,0,p;}" : "=r"(ok) : "r"(bar), "r"(ph) : "memory");
  return ok;
}
__device__ __forceinline__ bool mbar_test(uint32_t bar, uint32_t ph) {
  uint32_t ok;
  asm volatile("{.reg .pred p; mbarrier.test_wait.parity.shared::cta.b64 p,[%1],%2; selp.u32 %0,1,0,p;}" : "=r"(ok) : "r"(bar), "r"(ph) : "memory");
  return ok;
}
__device__ __forceinline__ void mbar_wait(uint32_t bar, uint32_t ph, int& left) {
  asm volatile("{\n.reg .pred p;\nW: mbarrier.try_wait.parity.shared::cta.b64 p,[%1],%2;\nadd.s32 %0,%0,-1;\nsetp.gt.and.s32 p,%0,0,!p;\n@p bra.uni W;\n}"
               : "+r"(left) : "r"(bar), "r"(ph) : "memory");
}
__device__ __forceinline__ bool elect() {
  uint32_t p;
  asm volatile("{.reg .pred p; elect.sync _|p,0xffffffff; selp.u32 %0,1,0,p;}" : "=r"(p));
  return p;
}
__device__ __forceinline__ int own_tid() {
  int r;
  asm volatile("{.reg .b32 t,l; mov.u32 t,%%tid.x; and.b32 l,t,31; and.b32 t,t,127; shfl.sync.idx.b32 %0,t,l,31,0xffffffff;}" : "=r"(r));
  return r;
}
__device__ __forceinline__ int fresh(int x) { asm volatile("" : "+r"(x)); return x; }
__device__ __forceinline__ void bar_sync(int id, int n) { asm volatile("bar.sync %0,%1;" ::"r"(id), "r"(n) : "memory"); }
__device__ __forceinline__ void bar_arrive(int id, int n) { asm volatile("bar.arrive %0,%1;" ::"r"(id), "r"(n) : "memory"); }
__device__ __forceinline__ bool bar_red_or(int id, int n, bool v) {
  uint32_t r;
  asm volatile("{\n .reg .pred p, q;\n setp.ne.u32 q, %3, 0;\n barrier.cta.red.or.pred p, %1, %2, q;\n selp.u32 %0, 1, 0, p;\n}" : "=r"(r) : "r"(id), "r"(n), "r"((uint32_t)v) : "memory");
  return r != 0;
}
__device__ __forceinline__ void cluster_sync() {
  asm volatile("barrier.cluster.arrive.release.aligned;" ::: "memory");
  asm volatile("barrier.cluster.wait.acquire.aligned;" ::: "memory");
}
__device__ __forceinline__ void cluster_sync_relaxed() {
  asm volatile("barrier.cluster.arrive.relaxed.aligned;" ::: "memory");
  asm volatile("barrier.cluster.wait.aligned;" ::: "memory");
}
__device__ __forceinline__ void fence_async() { asm volatile("fence.proxy.async.shared::cta;" ::: "memory"); }
__device__ __forceinline__ void bulk_g2s(uint32_t dst, const void* src, uint32_t bytes, uint32_t bar) {
  asm volatile("cp.async.bulk.shared::cluster.global.mbarrier::complete_tx::bytes [%0],[%1],%2,[%3];" ::"r"(dst), "l"(src), "r"(bytes), "r"(bar) : "memory");
}
__device__ __forceinline__ void bulk_g2s_mc(uint32_t dst, const void* src, uint32_t bytes, uint32_t bar) {
  asm volatile("cp.async.bulk.shared::cluster.global.mbarrier::complete_tx::bytes.multicast::cluster [%0],[%1],%2,[%3],%4;"
               ::"r"(dst), "l"(src), "r"(bytes), "r"(bar), "h"((uint16_t)7) : "memory");
}
__device__ __forceinline__ void bulk_s2g(void* dst, uint32_t src, uint32_t bytes) {
  asm volatile("cp.async.bulk.global.shared::cta.bulk_group [%0],[%1],%2;" ::"l"(dst), "r"(src), "r"(bytes) : "memory");
}
__device__ __forceinline__ void bulk_s2c(uint32_t dst, uint32_t src, uint32_t bytes, uint32_t bar) {
  asm volatile("cp.async.bulk.shared::cluster.shared::cta.mbarrier::complete_tx::bytes [%0],[%1],%2,[%3];" ::"r"(dst), "r"(src), "r"(bytes), "r"(bar) : "memory");
}
__device__ __forceinline__ void bulk_commit() { asm volatile("cp.async.bulk.commit_group;" ::: "memory"); }
__device__ __forceinline__ void bulk_wait_read() { asm volatile("cp.async.bulk.wait_group.read 0;" ::: "memory"); }
__device__ __forceinline__ void bulk_wait() { asm volatile("cp.async.bulk.wait_group 0;" ::: "memory"); }
__device__ __forceinline__ void tma2d(uint32_t dst, const CUtensorMap* tm, int c0, int c1, uint32_t bar) {
  asm volatile("cp.async.bulk.tensor.2d.shared::cluster.global.mbarrier::complete_tx::bytes [%0],[%1,{%3,%4}],[%2];"
               ::"r"(dst), "l"(tm), "r"(bar), "r"(c0), "r"(c1) : "memory");
}
__device__ __forceinline__ void tma2d_prefetch(const CUtensorMap* tm, int c0, int c1) {
  asm volatile("cp.async.bulk.prefetch.tensor.2d.L2.global.tile [%0,{%1,%2}];" ::"l"(tm), "r"(c0), "r"(c1) : "memory");
}
__device__ __forceinline__ void tma3d_mc(uint32_t dst, const CUtensorMap* tm, int c0, int c1, int c2, uint32_t bar) {
  asm volatile("cp.async.bulk.tensor.3d.shared::cluster.global.mbarrier::complete_tx::bytes.multicast::cluster [%0],[%1,{%3,%4,%5}],[%2],%6;"
               ::"r"(dst), "l"(tm), "r"(bar), "r"(c0), "r"(c1), "r"(c2), "h"((uint16_t)7) : "memory");
}
__device__ __forceinline__ uint32_t pack_bf16(float lo, float hi) {
  uint32_t r; asm("cvt.rn.bf16x2.f32 %0,%1,%2;" : "=r"(r) : "f"(hi), "f"(lo)); return r;
}
__device__ __forceinline__ uint32_t pack_h2(float lo, float hi) {
  uint32_t r; asm("cvt.rn.satfinite.f16x2.f32 %0,%1,%2;" : "=r"(r) : "f"(hi), "f"(lo)); return r;
}
__device__ __forceinline__ float2 unpack_h2(uint32_t x) {
  float2 r; asm("{.reg .b16 l,h; mov.b32 {l,h},%2; cvt.f32.f16 %0,l; cvt.f32.f16 %1,h;}" : "=f"(r.x), "=f"(r.y) : "r"(x)); return r;
}
__device__ __forceinline__ uint32_t add_h2(uint32_t a, uint32_t b) { uint32_t r; asm("add.rn.f16x2 %0,%1,%2;" : "=r"(r) : "r"(a), "r"(b)); return r; }
__device__ __forceinline__ uint32_t max_h2(uint32_t a, uint32_t b) { uint32_t r; asm("max.f16x2 %0,%1,%2;" : "=r"(r) : "r"(a), "r"(b)); return r; }
__device__ __forceinline__ float bf_lo(uint32_t x) { return __uint_as_float(x << 16); }
__device__ __forceinline__ float bf_hi(uint32_t x) { return __uint_as_float(x & 0xFFFF0000u); }
__device__ __forceinline__ float ex2(float x) { float y; asm("ex2.approx.ftz.f32 %0,%1;" : "=f"(y) : "f"(x)); return y; }
__device__ __forceinline__ void ldsm4t(uint32_t (&r)[4], uint32_t a) {
  asm volatile("ldmatrix.sync.aligned.m8n8.x4.trans.shared.b16 {%0,%1,%2,%3},[%4];" : "=r"(r[0]), "=r"(r[1]), "=r"(r[2]), "=r"(r[3]) : "r"(a) : "memory");
}
__device__ __forceinline__ void stsm4(uint32_t a, uint32_t r0, uint32_t r1, uint32_t r2, uint32_t r3) {
  asm volatile("stmatrix.sync.aligned.m8n8.x4.shared.b16 [%0],{%1,%2,%3,%4};" ::"r"(a), "r"(r0), "r"(r1), "r"(r2), "r"(r3) : "memory");
}
__device__ __forceinline__ void stsm4t(uint32_t a, uint32_t r0, uint32_t r1, uint32_t r2, uint32_t r3) {
  asm volatile("stmatrix.sync.aligned.m8n8.x4.trans.shared.b16 [%0],{%1,%2,%3,%4};" ::"r"(a), "r"(r0), "r"(r1), "r"(r2), "r"(r3) : "memory");
}
__device__ __forceinline__ void stsm2(uint32_t a, uint32_t r0, uint32_t r1) {
  asm volatile("stmatrix.sync.aligned.m8n8.x2.shared.b16 [%0],{%1,%2};" ::"r"(a), "r"(r0), "r"(r1) : "memory");
}
__device__ __forceinline__ void sts32(uint32_t a, uint32_t v) { asm volatile("st.shared.b32 [%0],%1;" ::"r"(a), "r"(v) : "memory"); }
__device__ __forceinline__ void sts128(uint32_t a, uint4 v) { asm volatile("st.shared.v4.b32 [%0],{%1,%2,%3,%4};" ::"r"(a), "r"(v.x), "r"(v.y), "r"(v.z), "r"(v.w) : "memory"); }
__device__ __forceinline__ uint32_t lds32(uint32_t a) { uint32_t v; asm volatile("ld.shared.b32 %0,[%1];" : "=r"(v) : "r"(a) : "memory"); return v; }
__device__ __forceinline__ uint2 lds64(uint32_t a) { uint2 v; asm volatile("ld.shared.v2.b32 {%0,%1},[%2];" : "=r"(v.x), "=r"(v.y) : "r"(a) : "memory"); return v; }
__device__ __forceinline__ uint4 lds128(uint32_t a) { uint4 v; asm volatile("ld.shared.v4.b32 {%0,%1,%2,%3},[%4];" : "=r"(v.x), "=r"(v.y), "=r"(v.z), "=r"(v.w) : "r"(a) : "memory"); return v; }
__device__ __forceinline__ void st_async1(uint32_t a, uint32_t x, uint32_t bar) {
  asm volatile("st.async.weak.shared::cluster.mbarrier::complete_tx::bytes.b32 [%0],%1,[%2];" ::"r"(a), "r"(x), "r"(bar) : "memory");
}
__device__ __forceinline__ void st_async2(uint32_t a, uint32_t x, uint32_t y, uint32_t bar) {
  asm volatile("st.async.weak.shared::cluster.mbarrier::complete_tx::bytes.v2.b32 [%0],{%1,%2},[%3];" ::"r"(a), "r"(x), "r"(y), "r"(bar) : "memory");
}
__device__ __forceinline__ void st_async4(uint32_t a, uint32_t x, uint32_t y, uint32_t z, uint32_t w, uint32_t bar) {
  asm volatile("st.async.weak.shared::cluster.mbarrier::complete_tx::bytes.v4.b32 [%0],{%1,%2,%3,%4},[%5];" ::"r"(a), "r"(x), "r"(y), "r"(z), "r"(w), "r"(bar) : "memory");
}
__device__ __forceinline__ uint32_t ld_relaxed(const void* p) {
  uint32_t v; asm volatile("ld.relaxed.gpu.global.u32 %0,[%1];" : "=r"(v) : "l"(p) : "memory"); return v;
}
__device__ __forceinline__ void st_relaxed(void* p, uint32_t v) { asm volatile("st.relaxed.gpu.global.b32 [%0],%1;" ::"l"(p), "r"(v) : "memory"); }
__device__ __forceinline__ void ld_msg16x4(uint4* x, const void* p) {
  asm volatile("{.reg .b128 a,b,c,d;\n ld.relaxed.gpu.global.b128 a,[%16]; ld.relaxed.gpu.global.b128 b,[%16+512];\n"
               "ld.relaxed.gpu.global.b128 c,[%16+1024]; ld.relaxed.gpu.global.b128 d,[%16+1536];\n"
               "mov.b128 {%0,%1,%2,%3},a; mov.b128 {%4,%5,%6,%7},b; mov.b128 {%8,%9,%10,%11},c; mov.b128 {%12,%13,%14,%15},d;}"
               : "=r"(x[0].x), "=r"(x[0].y), "=r"(x[0].z), "=r"(x[0].w), "=r"(x[1].x), "=r"(x[1].y), "=r"(x[1].z), "=r"(x[1].w),
                 "=r"(x[2].x), "=r"(x[2].y), "=r"(x[2].z), "=r"(x[2].w), "=r"(x[3].x), "=r"(x[3].y), "=r"(x[3].z), "=r"(x[3].w)
               : "l"(p) : "memory");
}
__device__ __forceinline__ uint32_t differ4(uint32_t a, uint32_t b, uint32_t c, uint32_t d, uint32_t t) {
  uint32_t r;
  asm volatile("{.reg .b32 u,v; lop3.b32 u,%1,%2,%5,0x7e; lop3.b32 v,%3,%4,%5,0x7e; or.b32 %0,u,v;}" : "=r"(r) : "r"(a), "r"(b), "r"(c), "r"(d), "r"(t));
  return r;
}
__device__ __forceinline__ void st_msg16(void* p, uint32_t x, uint32_t y, uint32_t z, uint32_t w) {
  asm volatile("{.reg .b128 r; mov.b128 r,{%1,%2,%3,%4}; st.relaxed.gpu.global.b128 [%0],r;}" ::"l"(p), "r"(x), "r"(y), "r"(z), "r"(w) : "memory");
}
__device__ __forceinline__ void ld_msg16x2(uint4* x, const void* p) {
  asm volatile("{.reg .b128 a,b;\n ld.relaxed.gpu.global.b128 a,[%8]; ld.relaxed.gpu.global.b128 b,[%8+512];\n"
               "mov.b128 {%0,%1,%2,%3},a; mov.b128 {%4,%5,%6,%7},b;}"
               : "=r"(x[0].x), "=r"(x[0].y), "=r"(x[0].z), "=r"(x[0].w), "=r"(x[1].x), "=r"(x[1].y), "=r"(x[1].z), "=r"(x[1].w)
               : "l"(p) : "memory");
}
__device__ __forceinline__ uint32_t ld_acquire(const void* p) {
  uint32_t v; asm volatile("ld.acquire.gpu.global.u32 %0,[%1];" : "=r"(v) : "l"(p) : "memory"); return v;
}
__device__ __forceinline__ float4 ld_relaxed4f(const void* p) {
  float4 v; asm volatile("ld.relaxed.gpu.global.v4.f32 {%0,%1,%2,%3},[%4];" : "=f"(v.x), "=f"(v.y), "=f"(v.z), "=f"(v.w) : "l"(p) : "memory"); return v;
}
__device__ __forceinline__ float2 ld_relaxed2f(const void* p) {
  float2 v; asm volatile("ld.relaxed.gpu.global.v2.f32 {%0,%1},[%2];" : "=f"(v.x), "=f"(v.y) : "l"(p) : "memory"); return v;
}
__device__ __forceinline__ uint4 ld_nc16(const void* p) {
  uint4 v; asm volatile("ld.global.nc.v4.u32 {%0,%1,%2,%3},[%4];" : "=r"(v.x), "=r"(v.y), "=r"(v.z), "=r"(v.w) : "l"(p)); return v;
}
__device__ __forceinline__ void prefetch_l2(const void* p) { asm volatile("prefetch.global.L2 [%0];" ::"l"(p)); }
__device__ __forceinline__ void fence_async_all() { asm volatile("fence.proxy.async.global;" ::: "memory"); }
__device__ __forceinline__ int launch_parity() { return __shfl_sync(0xffffffffu, ld_relaxed(&g_launch) & 1, 0); }
__device__ __forceinline__ void cnt_wait_warp(const uint32_t* p, uint32_t target, int& left) {
  while (__any_sync(0xffffffffu, ld_acquire(p) < target) && (left -= 16) > 0) {}
}
__device__ __forceinline__ void cnt_signal(uint32_t* p) { asm volatile("red.release.gpu.global.add.u32 [%0],1;" ::"l"(p) : "memory"); }

__host__ __device__ __forceinline__ constexpr uint64_t mkdesc(uint32_t addr, uint32_t lbo, uint32_t sbo) {
  return (uint64_t)((addr & 0x3FFFF) >> 4) | ((uint64_t)(lbo >> 4) << 16) | ((uint64_t)(sbo >> 4) << 32) | ((uint64_t)1 << 62);
}
__host__ __device__ __forceinline__ constexpr uint64_t mkdesc64(uint32_t addr, uint32_t lbo, uint32_t sbo) {
  return (uint64_t)((addr & 0x3FFFF) >> 4) | ((uint64_t)(lbo >> 4) << 16) | ((uint64_t)(sbo >> 4) << 32) | ((uint64_t)2 << 62);
}
__host__ __device__ __forceinline__ constexpr uint64_t mkdesc_ns(uint32_t addr, uint32_t lbo, uint32_t sbo) {
  return (uint64_t)((addr & 0x3FFFF) >> 4) | ((uint64_t)(lbo >> 4) << 16) | ((uint64_t)(sbo >> 4) << 32);
}
__device__ __forceinline__ void wg_fence() { asm volatile("wgmma.fence.sync.aligned;" ::: "memory"); }
__device__ __forceinline__ void wg_commit() { asm volatile("wgmma.commit_group.sync.aligned;" ::: "memory"); }
template <int N> __device__ __forceinline__ void wg_wait() { asm volatile("wgmma.wait_group.sync.aligned %0;" ::"n"(N) : "memory"); }

__device__ __forceinline__ void wgmma_rs32(float (&d)[16], const uint32_t (&a)[4], uint64_t db, int sc) {
  asm volatile("{.reg .pred p; setp.ne.b32 p,%21,0; wgmma.mma_async.sync.aligned.m64n32k16.f32.bf16.bf16 "
               "{%0,%1,%2,%3,%4,%5,%6,%7,%8,%9,%10,%11,%12,%13,%14,%15},{%16,%17,%18,%19},%20,p,1,1,0;}"
               : "+f"(d[0]), "+f"(d[1]), "+f"(d[2]), "+f"(d[3]), "+f"(d[4]), "+f"(d[5]), "+f"(d[6]), "+f"(d[7]),
                 "+f"(d[8]), "+f"(d[9]), "+f"(d[10]), "+f"(d[11]), "+f"(d[12]), "+f"(d[13]), "+f"(d[14]), "+f"(d[15])
               : "r"(a[0]), "r"(a[1]), "r"(a[2]), "r"(a[3]), "l"(db), "r"(sc));
}
__device__ __forceinline__ void wgmma_rt32(float (&d)[16], const uint32_t (&a)[4], uint64_t db, int sc) {
  asm volatile("{.reg .pred p; setp.ne.b32 p,%21,0; wgmma.mma_async.sync.aligned.m64n32k16.f32.bf16.bf16 "
               "{%0,%1,%2,%3,%4,%5,%6,%7,%8,%9,%10,%11,%12,%13,%14,%15},{%16,%17,%18,%19},%20,p,1,1,1;}"
               : "+f"(d[0]), "+f"(d[1]), "+f"(d[2]), "+f"(d[3]), "+f"(d[4]), "+f"(d[5]), "+f"(d[6]), "+f"(d[7]),
                 "+f"(d[8]), "+f"(d[9]), "+f"(d[10]), "+f"(d[11]), "+f"(d[12]), "+f"(d[13]), "+f"(d[14]), "+f"(d[15])
               : "r"(a[0]), "r"(a[1]), "r"(a[2]), "r"(a[3]), "l"(db), "r"(sc));
}
__device__ __forceinline__ void wgmma_rs48(float (&d)[24], const uint32_t (&a)[4], uint64_t db, int sc) {
  asm volatile("{.reg .pred p; setp.ne.b32 p,%29,0; wgmma.mma_async.sync.aligned.m64n48k16.f32.bf16.bf16 "
               "{%0,%1,%2,%3,%4,%5,%6,%7,%8,%9,%10,%11,%12,%13,%14,%15,%16,%17,%18,%19,%20,%21,%22,%23},{%24,%25,%26,%27},%28,p,1,1,0;}"
               : "+f"(d[0]), "+f"(d[1]), "+f"(d[2]), "+f"(d[3]), "+f"(d[4]), "+f"(d[5]), "+f"(d[6]), "+f"(d[7]),
                 "+f"(d[8]), "+f"(d[9]), "+f"(d[10]), "+f"(d[11]), "+f"(d[12]), "+f"(d[13]), "+f"(d[14]), "+f"(d[15]),
                 "+f"(d[16]), "+f"(d[17]), "+f"(d[18]), "+f"(d[19]), "+f"(d[20]), "+f"(d[21]), "+f"(d[22]), "+f"(d[23])
               : "r"(a[0]), "r"(a[1]), "r"(a[2]), "r"(a[3]), "l"(db), "r"(sc));
}
__device__ __forceinline__ void wgmma_ts32(float (&d)[16], uint64_t da, uint64_t db, int sc) {
  asm volatile("{.reg .pred p; setp.ne.b32 p,%18,0; wgmma.mma_async.sync.aligned.m64n32k16.f32.bf16.bf16 "
               "{%0,%1,%2,%3,%4,%5,%6,%7,%8,%9,%10,%11,%12,%13,%14,%15},%16,%17,p,1,1,1,0;}"
               : "+f"(d[0]), "+f"(d[1]), "+f"(d[2]), "+f"(d[3]), "+f"(d[4]), "+f"(d[5]), "+f"(d[6]), "+f"(d[7]),
                 "+f"(d[8]), "+f"(d[9]), "+f"(d[10]), "+f"(d[11]), "+f"(d[12]), "+f"(d[13]), "+f"(d[14]), "+f"(d[15])
               : "l"(da), "l"(db), "r"(sc));
}
__device__ __forceinline__ void wgmma_tt32(float (&d)[16], uint64_t da, uint64_t db, int sc) {
  asm volatile("{.reg .pred p; setp.ne.b32 p,%18,0; wgmma.mma_async.sync.aligned.m64n32k16.f32.bf16.bf16 "
               "{%0,%1,%2,%3,%4,%5,%6,%7,%8,%9,%10,%11,%12,%13,%14,%15},%16,%17,p,1,1,1,1;}"
               : "+f"(d[0]), "+f"(d[1]), "+f"(d[2]), "+f"(d[3]), "+f"(d[4]), "+f"(d[5]), "+f"(d[6]), "+f"(d[7]),
                 "+f"(d[8]), "+f"(d[9]), "+f"(d[10]), "+f"(d[11]), "+f"(d[12]), "+f"(d[13]), "+f"(d[14]), "+f"(d[15])
               : "l"(da), "l"(db), "r"(sc));
}
__device__ __forceinline__ void wgmma_ts48(float (&d)[24], uint64_t da, uint64_t db, int sc) {
  asm volatile("{.reg .pred p; setp.ne.b32 p,%26,0; wgmma.mma_async.sync.aligned.m64n48k16.f32.bf16.bf16 "
               "{%0,%1,%2,%3,%4,%5,%6,%7,%8,%9,%10,%11,%12,%13,%14,%15,%16,%17,%18,%19,%20,%21,%22,%23},%24,%25,p,1,1,1,0;}"
               : "+f"(d[0]), "+f"(d[1]), "+f"(d[2]), "+f"(d[3]), "+f"(d[4]), "+f"(d[5]), "+f"(d[6]), "+f"(d[7]),
                 "+f"(d[8]), "+f"(d[9]), "+f"(d[10]), "+f"(d[11]), "+f"(d[12]), "+f"(d[13]), "+f"(d[14]), "+f"(d[15]),
                 "+f"(d[16]), "+f"(d[17]), "+f"(d[18]), "+f"(d[19]), "+f"(d[20]), "+f"(d[21]), "+f"(d[22]), "+f"(d[23])
               : "l"(da), "l"(db), "r"(sc));
}
__device__ __forceinline__ void wgmma_ts64(float (&d)[32], uint64_t da, uint64_t db, int sc) {
  asm volatile("{.reg .pred p; setp.ne.b32 p,%34,0; wgmma.mma_async.sync.aligned.m64n64k16.f32.bf16.bf16 "
               "{%0,%1,%2,%3,%4,%5,%6,%7,%8,%9,%10,%11,%12,%13,%14,%15,%16,%17,%18,%19,%20,%21,%22,%23,%24,%25,%26,%27,%28,%29,%30,%31},%32,%33,p,1,1,1,0;}"
               : "+f"(d[0]), "+f"(d[1]), "+f"(d[2]), "+f"(d[3]), "+f"(d[4]), "+f"(d[5]), "+f"(d[6]), "+f"(d[7]),
                 "+f"(d[8]), "+f"(d[9]), "+f"(d[10]), "+f"(d[11]), "+f"(d[12]), "+f"(d[13]), "+f"(d[14]), "+f"(d[15]),
                 "+f"(d[16]), "+f"(d[17]), "+f"(d[18]), "+f"(d[19]), "+f"(d[20]), "+f"(d[21]), "+f"(d[22]), "+f"(d[23]),
                 "+f"(d[24]), "+f"(d[25]), "+f"(d[26]), "+f"(d[27]), "+f"(d[28]), "+f"(d[29]), "+f"(d[30]), "+f"(d[31])
               : "l"(da), "l"(db), "r"(sc));
}
__device__ __forceinline__ void wgmma_tt40(float (&d)[20], uint64_t da, uint64_t db, int sc) {
  asm volatile("{.reg .pred p; setp.ne.b32 p,%22,0; wgmma.mma_async.sync.aligned.m64n40k16.f32.bf16.bf16 "
               "{%0,%1,%2,%3,%4,%5,%6,%7,%8,%9,%10,%11,%12,%13,%14,%15,%16,%17,%18,%19},%20,%21,p,1,1,1,1;}"
               : "+f"(d[0]), "+f"(d[1]), "+f"(d[2]), "+f"(d[3]), "+f"(d[4]), "+f"(d[5]), "+f"(d[6]), "+f"(d[7]),
                 "+f"(d[8]), "+f"(d[9]), "+f"(d[10]), "+f"(d[11]), "+f"(d[12]), "+f"(d[13]), "+f"(d[14]), "+f"(d[15]),
                 "+f"(d[16]), "+f"(d[17]), "+f"(d[18]), "+f"(d[19])
               : "l"(da), "l"(db), "r"(sc));
}
__device__ __forceinline__ void wgmma_ss8(float (&d)[4], uint64_t da, uint64_t db, int sc) {
  asm volatile("{.reg .pred p; setp.ne.b32 p,%6,0; wgmma.mma_async.sync.aligned.m64n8k16.f32.bf16.bf16 "
               "{%0,%1,%2,%3},%4,%5,p,1,1,0,0;}"
               : "+f"(d[0]), "+f"(d[1]), "+f"(d[2]), "+f"(d[3])
               : "l"(da), "l"(db), "r"(sc));
}
__device__ __forceinline__ void wgmma_ss32(float (&d)[16], uint64_t da, uint64_t db, int sc) {
  asm volatile("{.reg .pred p; setp.ne.b32 p,%18,0; wgmma.mma_async.sync.aligned.m64n32k16.f32.bf16.bf16 "
               "{%0,%1,%2,%3,%4,%5,%6,%7,%8,%9,%10,%11,%12,%13,%14,%15},%16,%17,p,1,1,0,0;}"
               : "+f"(d[0]), "+f"(d[1]), "+f"(d[2]), "+f"(d[3]), "+f"(d[4]), "+f"(d[5]), "+f"(d[6]), "+f"(d[7]),
                 "+f"(d[8]), "+f"(d[9]), "+f"(d[10]), "+f"(d[11]), "+f"(d[12]), "+f"(d[13]), "+f"(d[14]), "+f"(d[15])
               : "l"(da), "l"(db), "r"(sc));
}
__device__ __forceinline__ void wgmma_tt16(float (&d)[8], uint64_t da, uint64_t db, int sc) {
  asm volatile("{.reg .pred p; setp.ne.b32 p,%10,0; wgmma.mma_async.sync.aligned.m64n16k16.f32.bf16.bf16 "
               "{%0,%1,%2,%3,%4,%5,%6,%7},%8,%9,p,1,1,1,1;}"
               : "+f"(d[0]), "+f"(d[1]), "+f"(d[2]), "+f"(d[3]), "+f"(d[4]), "+f"(d[5]), "+f"(d[6]), "+f"(d[7])
               : "l"(da), "l"(db), "r"(sc));
}

__device__ __forceinline__ void ln_row_load(const bf16* __restrict__ x, uint4 (&v)[3], int row, int lane) {
  const uint4* src = reinterpret_cast<const uint4*>(x + (size_t)row * DM);
  v[0] = ld_nc16(src + lane); v[1] = ld_nc16(src + lane + 32); v[2] = ld_nc16(src + 64 + (lane & 15));
}
__device__ __forceinline__ void ln_row(uint4 (&v)[3], int lane) {
  if (lane >= 16) v[2] = make_uint4(0, 0, 0, 0);
  float s = 0.f;
#pragma unroll
  for (int i = 0; i < 3; i++) {
    s += bf_lo(v[i].x) + bf_hi(v[i].x) + bf_lo(v[i].y) + bf_hi(v[i].y) + bf_lo(v[i].z) + bf_hi(v[i].z) + bf_lo(v[i].w) + bf_hi(v[i].w);
  }
#pragma unroll
  for (int o = 16; o > 0; o >>= 1) s += __shfl_xor_sync(0xffffffffu, s, o);
  const float mean = s * (1.f / DM);
  float q = 0.f;
#pragma unroll
  for (int i = 0; i < 3; i++) {
    if (i < 2 || lane < 16) {
      const uint32_t w[4] = {v[i].x, v[i].y, v[i].z, v[i].w};
#pragma unroll
      for (int j = 0; j < 4; j++) { float a = bf_lo(w[j]) - mean, b = bf_hi(w[j]) - mean; q += a * a + b * b; }
    }
  }
#pragma unroll
  for (int o = 16; o > 0; o >>= 1) q += __shfl_xor_sync(0xffffffffu, q, o);
  const float rstd = rsqrtf(q * (1.f / DM) + 1e-5f);
#pragma unroll
  for (int i = 0; i < 3; i++) {
    if (i < 2 || lane < 16) {
      uint4 o;
      o.x = pack_bf16((bf_lo(v[i].x) - mean) * rstd, (bf_hi(v[i].x) - mean) * rstd);
      o.y = pack_bf16((bf_lo(v[i].y) - mean) * rstd, (bf_hi(v[i].y) - mean) * rstd);
      o.z = pack_bf16((bf_lo(v[i].z) - mean) * rstd, (bf_hi(v[i].z) - mean) * rstd);
      o.w = pack_bf16((bf_lo(v[i].w) - mean) * rstd, (bf_hi(v[i].w) - mean) * rstd);
      v[i] = o;
    }
  }
}

namespace C {
constexpr int OFF_WK = 0;
constexpr int OFF_WO = 81920;
constexpr int OFF_WXQ = 131072;
constexpr int OFF_WXV = 133120;
constexpr int STAGE_Q = 51200, STAGE_V = 133120, STAGE_X = 215040;
constexpr int OFF_R = 139264;
constexpr int OFF_OG = OFF_R + 16384;
constexpr int OFF_RING = 180224;
constexpr int OFF_SCR = OFF_RING + 49152;
constexpr int SLOT = 6144;
__host__ __device__ constexpr int slot_off(int c) { return c < 3 ? OFF_R + 22528 + c * SLOT : c < 6 ? OFF_RING + (c - 3) * SLOT : OFF_RING + 20480 + (c - 6) * SLOT; }
constexpr int OFF_QT = OFF_RING;
constexpr int OFF_KT = OFF_RING + 10240;
constexpr int OFF_VT = OFF_RING + 20480;
constexpr int OFF_P = OFF_RING + 30720;
constexpr int OFF_XL = OFF_P + 7680;
constexpr int OFF_XM = OFF_XL + 10752;
__host__ __device__ constexpr int xl_off(int w) { return OFF_XL + (w ? w * 1152 - 512 : 0); }
constexpr int OFF_BAR = 231424;
constexpr int OFF_TS = OFF_BAR + 256;
constexpr int OFF_INV = OFF_BAR + 768;
constexpr int SMEM = 232448;
constexpr uint32_t SB0 = 1024;
constexpr int BAR_F0 = OFF_BAR, BAR_F1 = OFF_BAR + 8, BAR_F2 = OFF_BAR + 16,
              BAR_RID = OFF_BAR + 24, BAR_M = OFF_BAR + 32,
              BAR_X = OFF_BAR + 64,
              BAR_ROT = OFF_BAR + 104, BAR_OG = OFF_BAR + 112, BAR_OG2 = OFF_BAR + 120,
              BAR_W1 = OFF_BAR + 128, BAR_W2 = OFF_BAR + 136, BAR_W3 = OFF_BAR + 144, BAR_XE = OFF_BAR + 152, BAR_OE = OFF_BAR + 160,
              BAR_RQ = OFF_BAR + 168, BAR_VF = OFF_BAR + 176, BAR_RF = OFF_BAR + 184, BAR_RE = OFF_BAR + 192, BAR_OS = OFF_BAR + 200,
              OFF_SEL = OFF_BAR + 208;
__device__ constexpr int bar_bytes(int i) {
  return i < 2 ? 3 * SLOT : i == 2 ? 4 * SLOT : i == 3 ? 20480 : i < 8 ? 5120 : i == 8 ? 2560 : i == 9 || i == 12 ? 1280 : i < 12 ? 2304 :
         i == 13 ? 16384 : i == 14 ? 2048 : 16384 + 2048;
}
constexpr int NB_P2 = 0, NB_M = 1, NB_QK = 2, NB_P = 3, NB_V = 4, NB_MR = 5, NB_GO = 6, NB_O = 7, NB_BQ = 8, NB_BV = 9, NB_S = 10, NB_X = 11, NB_M2 = 15;
#define B1 300
#define B2 200
#define B3 2100
#define OSP 0
#define PL2 1
#define PL1 1
#define OGF 1
#define PFD 3
constexpr float SCL = 0.07216878364870322f * 1.4426950408889634f;
__host__ __device__ constexpr int wo_off(int u) { return u < 2 ? OFF_RING + u * 8192 : u < 8 ? OFF_WO + (u - 2) * 8192 : OFF_R + (u - 8) * 8192; }
__host__ __device__ constexpr int wo_col(int u, int rank) { return u == 0 ? 576 : (3 * rank + (u - 1) % 3) * 64; }
__host__ __device__ constexpr int wo_row(int u, int cta) { return (cta / 3) * DH + ((cta + 3 - (u ? (u - 1) / 3 : 0)) % 3) * 64; }
}

struct ChainArgs {
  uint8_t* xn;
  uint8_t* oimg;
  uint8_t* mbuf;
  uint8_t* mail;
  uint8_t* rot;
  Counters* cnt;
  const bf16 *x0, *mem0, *wo;
};

template <int NK>
__device__ __forceinline__ void load_wfrags(uint32_t (&a)[NK][4], uint32_t base, int w, int lane) {
  const int i = lane >> 3, r = lane & 7;
  const int chunk = 2 * w + (i & 1);
  const uint32_t a0 = base + (r + (i >> 1) * 8) * 128 + ((chunk ^ r) << 4);
#pragma unroll
  for (int k = 0; k < NK; k++) ldsm4t(a[k], a0 + k * 2048);
}
__device__ __forceinline__ uint64_t desc2(uint32_t lo, uint32_t hi) { uint64_t d; asm("mov.b64 %0,{%1,%2};" : "=l"(d) : "r"(lo), "r"(hi)); return d; }
__host__ __device__ __forceinline__ constexpr uint64_t wdesc(int off) { return mkdesc(C::SB0 + off, 8192, 1024); }
__host__ __device__ __forceinline__ constexpr uint64_t rdesc(int k) { return mkdesc_ns(C::SB0 + C::OFF_R + k * 256, 128, 10240); }
__host__ __device__ __forceinline__ constexpr uint64_t tdesc(int k) { return mkdesc_ns(C::SB0 + C::slot_off(k >> 2) + (k & 3) * 256, 128, 1024); }
template <int N>
__device__ __forceinline__ void store_pair(const float (&d)[N], int j0, int j1, uint32_t a) {
  stsm4(a, pack_bf16(d[4 * j0], d[4 * j0 + 1]), pack_bf16(d[4 * j0 + 2], d[4 * j0 + 3]), pack_bf16(d[4 * j1], d[4 * j1 + 1]), pack_bf16(d[4 * j1 + 2], d[4 * j1 + 3]));
}
__device__ __forceinline__ uint32_t tile_lane(int tid) { return (((tid >> 4) & 6) + ((tid >> 3) & 1)) * 1280 + (tid & 7) * 16; }
__device__ __forceinline__ void load_chunk(const CUtensorMap& tmX, uint32_t sb, int b, int c, int off, int bar) {
  tma3d_mc(sb + off, &tmX, c * 256, 4 * b, 0, sb + bar);
}
template <int BAR>
__device__ __forceinline__ void arrive_all(uint32_t peer, int i) {
  asm volatile("{.reg .pred p; setp.lt.u32 p,%1,3; @p mbarrier.arrive.shared::cluster.b64 _,[%0+%2];}" ::"r"(peer), "r"(i), "n"(BAR) : "memory");
}
__device__ __forceinline__ void probe(const ChainArgs& a, uint32_t sb, int job, int tries, int cta, int unit, int warp) {
  uint8_t* p = job < 5 ? a.mbuf + ((1 << job) >> 1) * 8192 + cta * 32 + (warp & 4) : a.mail + (size_t)min(unit, NUNIT) * MAIL_UNIT + warp * 128;
  uint32_t best[2] = {SENT, SENT};
#pragma unroll 1
  for (int r = 0; r < 2 * tries; r++) {
    const uint32_t t0 = clk32();
    uint32_t v;
    asm volatile("atom.relaxed.gpu.global.exch.b32 %0,[%1],-1;" : "=r"(v) : "l"(p + (r & 1) * 4096) : "memory");
    uint32_t dt = t0 - 1;
    asm volatile("{.reg .b64 c; .reg .pred p; setp.eq.b32 p,%1,-1; @p mov.u64 c,%%clock64; @p cvt.u32.u64 %0,c;}" : "+r"(dt) : "r"(v) : "memory");
    dt -= t0;
    if (r & 1) best[1] = min(best[1], dt); else best[0] = min(best[0], dt);
  }
  asm volatile("red.shared.min.u32 [%0],%1; red.shared.min.u32 [%0+4],%2;" ::"r"(sb + C::OFF_SEL + job * 8), "r"(best[0]), "r"(best[1]) : "memory");
}
#define WPF 3
__device__ __forceinline__ void load_piece(const CUtensorMap& tmWq, const CUtensorMap& tmWk, const CUtensorMap& tmWv, uint32_t sb, int col, int i) {
  using namespace C;
  const uint32_t bar = sb + BAR_M + 8 * (i & 3);
  mbar_expect_tx(bar, 16384);
  if (i < 10) { tma2d(sb + STAGE_Q + i * 8192, &tmWq, col, i * 64, bar); tma2d(sb + STAGE_V + i * 8192, &tmWv, col, i * 64, bar); }
  else { tma2d(sb + OFF_WK + (i - 10) * 16384, &tmWk, col, (i - 10) * 128, bar); tma2d(sb + OFF_WK + (i - 10) * 16384 + 8192, &tmWk, col, (i - 10) * 128 + 64, bar); }
}
struct ChainDesc { uint64_t pad[8], td[40], rd[40], kd[44], od[40], gd[12], sd[16], vd[6], pd[12]; };
constexpr ChainDesc chain_desc() {
  using namespace C;
  ChainDesc a = {};
  for (int k = 0; k < 40; k++) { a.td[k] = tdesc(k); a.rd[k] = rdesc(k); a.kd[k] = wdesc(OFF_WK + k * 2048); a.od[k] = wdesc(wo_off(k >> 2) + (k & 3) * 2048); }
  for (int k = 0; k < 4; k++) a.kd[40 + k] = wdesc(OFF_WXQ + k * 2048);
  for (int k = 0; k < 12; k++) a.gd[k] = mkdesc_ns(SB0 + OFF_OG + k * 512, 256, 128);
  for (int k = 0; k < 8; k++) {
    a.sd[2 * k] = mkdesc_ns(SB0 + OFF_QT + (k >> 1) * 2560 + (k & 1) * 256, 1280, 128);
    a.sd[2 * k + 1] = mkdesc_ns(SB0 + OFF_KT + (k >> 1) * 2560 + (k & 1) * 640, 1280, 128);
  }
  for (int k = 0; k < 6; k++) a.vd[k] = mkdesc_ns(SB0 + OFF_VT + (k / 3) * 640 + (k % 3) * 256, 128, 1280);
  for (int k = 0; k < 12; k++) a.pd[k] = mkdesc_ns(SB0 + OFF_P + (k < 3 ? 0 : k < 6 ? 9 : k < 9 ? 1 : 5) * 768 + (k % 3) * 256, 128, 768);
  return a;
}
__constant__ ChainDesc cd = chain_desc();
__device__ __forceinline__ uint32_t keep_u(uint32_t v) { return __shfl_sync(0xffffffffu, v, 0); }
__device__ __forceinline__ uint32_t keep(uint32_t v, int tid) { return __shfl_sync(0xffffffffu, v, tid); }

#define OSK 7
#define VE 3
#define DN 1
#define F1L 2
#define NT1 8
#define B1T 2
#define RIDL 0
#define S9E 1
#define F2K 16
#define PVE 0
#define QGA 3
#define NOX 0
#define VD 0
#define TD(k) cd.td[k]
#define RD(k) cd.rd[k]
__device__ __forceinline__ uint32_t quad_max_h2(uint32_t m) {
  const uint32_t a = __shfl_xor_sync(0xffffffffu, m, 1), b = __shfl_xor_sync(0xffffffffu, m, 2), c = __shfl_xor_sync(0xffffffffu, m, 3);
  return max_h2(max_h2(m, a), max_h2(b, c));
}
__device__ __forceinline__ uint32_t diag_mask(int lane) {
  const int dg = (lane >> 2) - 2 * (lane & 3);
  return dg >= 1 ? 0u : dg == 0 ? 0xFC000000u : 0xFC00FC00u;
}
__device__ __forceinline__ float quad_sum(float m) {
  const float a = __shfl_xor_sync(0xffffffffu, m, 1), b = __shfl_xor_sync(0xffffffffu, m, 2), c = __shfl_xor_sync(0xffffffffu, m, 3);
  return (m + a) + (b + c);
}
__device__ __forceinline__ float rcp(float x) { float y; asm("rcp.approx.ftz.f32 %0,%1;" : "=f"(y) : "f"(x)); return y; }
__device__ __forceinline__ void p_store(uint32_t a, uint32_t p0, uint32_t p1, uint32_t p2, uint32_t p3, uint32_t p4) {
  stsm4(a, p0, p1, p2, p3);
  stsm2(a + 512, p4, 0u);
}

__device__ __forceinline__ void chain_q(const CUtensorMap& tmWk, const CUtensorMap& tmWo, const CUtensorMap& tmX, const ChainArgs& a,
                                        const uint32_t sb, const int tid0, const int cta, const int rank, Counters* cnt) {
  using namespace C;
  asm volatile("setmaxnreg.inc.sync.aligned.u32 208;");
  int left = SPIN_BUDGET;
  const uint32_t peer = keep(mapa(sb, (tid0 & 3) % 3), tid0);
  uint32_t wf[39][4];
  cnt_wait_warp(&cnt[CN_Z][0][32], 96, left);
  __threadfence();
  fence_async_all();
  mbar_wait(sb + BAR_W1, 0, left);
  PTS(4);
  load_wfrags<39>(wf, sb + STAGE_Q, tid0 >> 5, tid0 & 31);
  cluster_sync_relaxed();
  PTS(5);
  const uint32_t qa = sb + OFF_QT + tile_lane(tid0) + ((tid0 & 16) ? 9 * 128 : 0);
  const int dq = (tid0 & 16) ? -128 : 128;
  const int warp = __shfl_sync(0xffffffffu, tid0 >> 5, 0);
  const uint32_t nb = keep(bar_bytes(tid0), tid0);
  if (tid0 < 4) mbar_expect_tx(sb + OFF_BAR + 8 * tid0, nb);
  if (tid0 == 0) {
    load_chunk(tmX, sb, 0, rank, slot_off(rank), BAR_F0);
    load_chunk(tmX, sb, 0, 3 + rank, slot_off(3 + rank), BAR_F1);
    mbar_expect_tx(sb + BAR_W2, 32768);
    for (int i = 6; i < 10; i++) tma2d(sb + OFF_WK + i * 8192, &tmWk, (cta / 3) * DH + rank * 64, i * 64, sb + BAR_W2);
    mbar_expect_tx(sb + BAR_W3, 6 * 8192);
    for (int u = 2; u < 8; u++) tma2d(sb + wo_off(u), &tmWo, wo_col(u, rank), wo_row(u, cta), sb + BAR_W3);
  }
  __syncwarp();

  for (int b = 0; b < NS; b++) {
    const int ph = b & 1;
    {
      float d[24];
      mbar_wait(sb + BAR_F0, ph, left);
      if (b > 0) bar_sync(NB_GO, 256);
      TSB(b, 16);
      wg_fence();
#pragma unroll
      for (int k = 0; k < 12; k++) wgmma_rs48(d, wf[k], TD(k), k);
      wg_commit();
      mbar_wait(sb + BAR_F1, ph, left);
      wg_fence();
#pragma unroll
      for (int k = 12; k < F2K; k++) wgmma_rs48(d, wf[k], TD(k), 1);
      wg_commit();
      wg_wait<1>();
      arrive_all<BAR_RE>(peer, tid0 - 32);
      if (warp == 0) {
        mbar_wait(sb + BAR_VF, ph, left);
        if (elect()) {
          load_chunk(tmX, sb, b, 6 + rank, slot_off(6) + rank * SLOT, BAR_F2);
          if (rank == 0) load_chunk(tmX, sb, b, 9, slot_off(9), BAR_F2);
        }
        TS(b, 21);
      }
      wg_fence();
#pragma unroll
      for (int k = F2K; k < 24; k++) wgmma_rs48(d, wf[k], TD(k), 1);
      if (RIDL == 0 && warp == 0 && rank) {
        mbar_wait(sb + BAR_RE, ph, left);
        if (elect()) bulk_g2s_mc(sb + OFF_R + (1 + rank) * 10240, a.xn + (size_t)(4 * b + 3 + (rank - 1) * (256 - 4 * LAG)) * 10240, 10240, sb + BAR_RID);
      }
      mbar_wait(sb + BAR_F2, ph, left);
      if (RIDL == 1 && warp == 0 && rank) {
        mbar_wait(sb + BAR_RE, ph, left);
        if (elect()) bulk_g2s_mc(sb + OFF_R + (1 + rank) * 10240, a.xn + (size_t)(4 * b + 3 + (rank - 1) * (256 - 4 * LAG)) * 10240, 10240, sb + BAR_RID);
      }
      wg_fence();
#pragma unroll
      for (int k = 24; k < 39; k++) wgmma_rs48(d, wf[k], TD(k), 1);
      wgmma_ts48(d, cd.kd[40], TD(39), 1);
      wg_commit();
      wg_wait<0>();
      TS(b, 17);
      bar_arrive(NB_BQ, 256);
      arrive_all<BAR_XE>(peer, tid0 - 32);
      bar_sync(NB_BV, 256);
#pragma unroll
      for (int j = 0; j < 3; j++) store_pair(d, j, j + 3, qa + (4 - j) * dq);
    }
    {
      float d[16];
      bar_sync(NB_M2, 256);
      TSB(b, 18);
      wg_fence();
#pragma unroll
      for (int k = 0; k < 39; k++) wgmma_rs32(d, wf[k], RD(k), k);
      wgmma_ts32(d, cd.kd[40], RD(39), 1);
      wg_commit();
      if (tid0 < 16) mbar_expect_tx(sb + OFF_BAR + 8 * tid0, nb);
      wg_wait<0>();
      TS(b, 19);
      store_pair(d, 0, 1, qa);
      store_pair(d, 2, 3, qa + dq);
      fence_async();
      bar_arrive(NB_QK, 384);
    }
    const int bn = b + 1;
    {
      const int lane = fresh(tid0) & 31;
      const bool up = warp >= 2, outer = warp == 0 || warp == 3;
      const uint32_t xo = xl_off(warp), ob = sb + xo + lane * 16;
      const uint32_t dm = diag_mask(lane);
      if (warp == 0) {
        bar_sync(NB_S, 288);
        if (bn < NS && elect()) bulk_g2s(sb + wo_off(0), a.rot + (size_t)cta * 32768, 16384, sb + BAR_ROT);
        __syncwarp();
      }
      bar_sync(NB_X + warp, 64);
      fence_async();
      if (elect()) {
        const uint32_t r1 = mapa(sb, (rank + 1) % 3), r2 = mapa(sb, (rank + 2) % 3), n = outer ? 640 : 1152;
        bulk_s2c(r1 + xo + 3584, sb + xo + 7168, n, r1 + BAR_X + 8 + 8 * warp);
        bulk_s2c(r2 + xo, sb + xo + 7168, n, r2 + BAR_X + 8 + 8 * warp);
      }
      __syncwarp();
      mbar_wait(sb + BAR_X + 8 + 8 * warp, ph, left);
      {
        float z[10];
        const uint4 s = lds128(ob + 7168), u = lds128(ob), v = lds128(ob + 3584);
        const uint32_t ts = lds32(ob + 7168 + 512 - lane * 12), tu = lds32(ob + 512 - lane * 12), tv = lds32(ob + 3584 + 512 - lane * 12);
        const uint32_t h[5] = {add_h2(add_h2(s.x, u.x), v.x), add_h2(add_h2(s.y, u.y), v.y), add_h2(add_h2(add_h2(s.z, outer ? 0u : dm), u.z), v.z),
                               add_h2(add_h2(s.w, u.w), v.w), add_h2(add_h2(add_h2(ts, dm), tu), tv)};
        const uint32_t ma = max_h2(max_h2(h[0], h[1]), h[2]), mb = max_h2(h[3], h[4]);
        uint32_t m = max_h2(__byte_perm(ma, mb, 0x5410), __byte_perm(ma, mb, 0x7632));
        if (outer) m = max_h2(m, __byte_perm(m, m, 0x1032));
        const float2 mf = unpack_h2(quad_max_h2(m));
        const float m0 = -SCL * mf.x, m1 = -SCL * mf.y;
#pragma unroll
        for (int j = 0; j < 5; j++) {
          const float2 f = unpack_h2(h[j]);
          z[2 * j] = ex2(fmaf(f.x, SCL, j < 3 ? m0 : m1)); z[2 * j + 1] = ex2(fmaf(f.y, SCL, j < 3 ? m0 : m1));
        }
        float s0 = ((z[0] + z[1]) + (z[2] + z[3])) + (z[4] + z[5]), s1 = (z[6] + z[7]) + (z[8] + z[9]);
        if (outer) s0 = s1 = s0 + s1;
        s0 += __shfl_xor_sync(0xffffffffu, s0, 1); s1 += __shfl_xor_sync(0xffffffffu, s1, 1);
        s0 = rcp(s0 + __shfl_xor_sync(0xffffffffu, s0, 2)); s1 = rcp(s1 + __shfl_xor_sync(0xffffffffu, s1, 2));
        const uint32_t p3 = pack_bf16(z[6] * s1, z[7] * s1), p4 = pack_bf16(z[8] * s1, z[9] * s1);
        p_store(sb + OFF_P + (2 * warp + (up ? 2 : 1)) * 768 + lane * 16, pack_bf16(z[0] * s0, z[1] * s0), pack_bf16(z[2] * s0, z[3] * s0), pack_bf16(z[4] * s0, z[5] * s0),
                outer ? p3 : 0u, outer ? p4 : 0u);
        if (!outer) p_store(sb + OFF_P + (up ? 4 * 768 : 5 * 768) + lane * 16, p3, p4, 0u, 0u, 0u);
      }
      fence_async();
      bar_arrive(NB_V, 384);
      TS(b, 31);
    }
  }
  if (left <= 0) g_err = 1;
}

__device__ __forceinline__ void chain_v(const ChainArgs& a, const uint32_t sb, const int tid0, const int cta, const int rank, Counters* cnt) {
  using namespace C;
  asm volatile("setmaxnreg.inc.sync.aligned.u32 224;");
  int left = SPIN_BUDGET;
  const uint32_t peer = keep(mapa(sb, (tid0 & 3) % 3), tid0);
  uint32_t wf[37][4];
  __threadfence();
  fence_async_all();
  mbar_wait(sb + BAR_W1, 0, left);
  load_wfrags<37>(wf, sb + STAGE_V + 3 * 2048, tid0 >> 5, tid0 & 31);
  cluster_sync_relaxed();
  uint32_t mo = (24 * rank + (tid0 >> 4)) * MAIL_UNIT + (cta / 24) * 8192 + ((cta / 3) & 7) * 256 + (tid0 & 15) * 16;
  const int blk9 = cta / 24 + (cta % 24 < 16 ? 0 : 4);
  uint32_t mo9 = (72 + (tid0 >> 3)) * MAIL_UNIT + blk9 * 8192 + ((cta % 24) & 15) * 128 + (tid0 & 7) * 16;
  mbar_wait(sb + BAR_W2, 0, left);
  const uint32_t ka = __shfl_sync(0xffffffffu, sb + OFF_KT + tile_lane(tid0) + ((tid0 & 16) ? 640 : 0), tid0);
  const int warp = __shfl_sync(0xffffffffu, tid0 >> 5, 0);

  for (int b = 0; b < NS; b++) {
    const int ph = b & 1;
    {
      float dv[24], dk[24];
#define VK(K0, K1)                                                   \
  wg_fence();                                                        \
  _Pragma("unroll") for (int k = K0; k < K1; k++) {                  \
    if (k < 3) wgmma_ts48(dv, cd.kd[41 + k], TD(k), k);               \
    else wgmma_rs48(dv, wf[k - 3], TD(k), 1);                        \
    wgmma_ts48(dk, cd.kd[k], TD(k), k);                               \
  }                                                                  \
  wg_commit();
      mbar_wait(sb + BAR_F0, ph, left);
      TSB(b, 22);
      VK(0, 12)
      mbar_wait(sb + BAR_F1, ph, left);
      VK(12, 15)
      wg_wait<1>();
      arrive_all<BAR_RE>(peer, tid0);
      VK(15, 24)
      TS(b, 23);
      mbar_wait(sb + BAR_F2, ph, left);
      VK(24, 27)
      wg_wait<1>();
      bar_arrive(NB_BV, 256);
      VK(27, 40)
#undef VK
      wg_wait<0>();
      TS(b, 24);
      arrive_all<BAR_XE>(peer, tid0);
      bar_sync(NB_BQ, 256);
#pragma unroll
      for (int j = 0; j < 3; j++) {
        store_pair(dk, j, j + 3, ka + (1 + j) * 128);
        store_pair(dv, j, j + 3, ka + 10240 + (1 + j) * 128);
        __syncwarp();
      }
    }
    const bool succ = b + 1 < NS;
    {
      float e[16];
      fence_async();
      bar_arrive(NB_QK, 384);
      if (warp == 1 && b > 0) {
        mbar_wait(sb + BAR_OS, ph, left);
        if (elect()) cnt_signal(&cnt[CN_O][b - 1][(cta >> 4) * 32]);
        __syncwarp();
      }
      if (VE) {
        bar_sync(NB_M, 256);
        wg_fence();
#pragma unroll
        for (int k = 3; k < 3 + VE; k++) wgmma_rs32(e, wf[k - 3], RD(k), k - 3);
      }
      bar_sync(NB_S, 288);
      wg_fence();
#pragma unroll
      for (int k = 0; k < 3; k++) wgmma_ts32(e, cd.kd[41 + k], RD(k), VE || k);
#pragma unroll
      for (int k = 3 + VE; k < 40; k++) wgmma_rs32(e, wf[k - 3], RD(k), 1);
      wg_commit();
      wg_wait<0>();
      TS(b, 26);
      store_pair(e, 0, 1, ka + 10240);
      store_pair(e, 2, 3, ka + 10240 + 4 * 128);
      fence_async();
      arrive_all<BAR_OE>(peer, tid0 - 32);
      if (!succ) { bar_arrive(NB_V, 384); break; }
      if (warp == 0 && elect()) bulk_g2s(sb + wo_off(8), a.rot + (size_t)cta * 32768 + 16384, 16384, sb + BAR_OG2);
      __syncwarp();
    if (b == 0) {
      const uint32_t *p = &cnt[CN_S][0][0] + (24 * rank + (tid0 >> 4)) * 32, *q = &cnt[CN_S][0][0] + (72 + (tid0 >> 3)) * 32;
      uint32_t v0, v1, v2, v3;
      do {
        v0 = ld_relaxed(p); v1 = ld_relaxed(p + 256); v2 = ld_relaxed(p + 512); v3 = ld_relaxed(q);
      } while (__any_sync(0xffffffffu, !(v0 & v1 & v2 & v3 & 256)) && (left -= 16) > 0);
      __threadfence();
      mo |= ((v0 >> (cta / 24)) & 1) * 0x1003;
      mo ^= ((v1 >> (cta / 24)) & 1) | (((v2 >> (cta / 24)) & 1) << 1);
      mo9 |= ((v3 >> blk9) & 1) << 12;
    }
    }
    bar_sync(NB_P, 192);
    TSB(b, 27);
    {
      float o0[4], o1[4];
      wg_fence();
#pragma unroll
      for (int q = 0; q < 3; q++) {
        wgmma_ss8(o0, cd.vd[q], cd.pd[q], q);
        wgmma_ss8(o1, cd.vd[3 + q], cd.pd[3 + q], q);
      }
      wg_commit();
      bar_sync(NB_P2, 192);
      const uint2 r0 = lds64(sb + OFF_INV + (tid0 & 3) * 8), r1 = lds64(sb + OFF_INV + 32 + (tid0 & 3) * 8);
      wg_wait<0>();
      TS(b, 6);
      const float a0 = __uint_as_float(r0.x), a1 = __uint_as_float(r0.y), b0 = __uint_as_float(r1.x), b1 = __uint_as_float(r1.y);
      stsm4(sb + OFF_OG + tid0 * 16, pack_bf16(o0[0] * a0, o0[1] * a1), pack_bf16(o1[0] * b0, o1[1] * b1), pack_bf16(o0[2] * a0, o0[3] * a1),
            pack_bf16(o1[2] * b0, o1[3] * b1));
      fence_async();
    }
    bar_sync(NB_O, 160);
    TSB(b, 7);
    {
      float acc[4][8];
      wg_fence();
#pragma unroll
      for (int kk = 0; kk < 4; kk++) wgmma_tt16(acc[3], cd.od[kk], cd.gd[kk], kk);
#pragma unroll
      for (int i = 0; i < 3; i++)
#pragma unroll
        for (int kk = 0; kk < 4; kk++) {
          wgmma_tt16(acc[i], cd.od[4 + 4 * i + kk], cd.gd[kk], kk);
          if (i != 1 && kk == 3) wg_commit();
        }
      wg_wait<1>();
      if (!F1L) arrive_all<BAR_RQ>(peer, tid0);
      uint8_t* mb = a.mail + ph * 2048;
      const uint32_t tag = (b >> 1) & 1;
#define SEND(O, I) st_msg16(mb + (O), (pack_h2(acc[I][0], acc[I][2]) & ~1u) | tag, pack_h2(acc[I][1], acc[I][3]), \
                            pack_h2(acc[I][4], acc[I][6]), pack_h2(acc[I][5], acc[I][7]))
      if (S9E == 1) { SEND(mo9, 3); __syncwarp(); }
      mbar_wait(sb + BAR_OG, ph, left);
      if (F1L == 1) arrive_all<BAR_RQ>(peer, tid0);
      if (S9E == 2) { SEND(mo9, 3); __syncwarp(); }
      TS(b, 8);
      wg_fence();
#pragma unroll
      for (int k = 0; k < 12; k++) wgmma_tt16(acc[k >> 2], cd.od[16 + k], cd.gd[4 + (k & 3)], 1);
      mbar_wait(sb + BAR_OG2, ph, left);
      if (F1L == 2) arrive_all<BAR_RQ>(peer, tid0);
      TS(b, 29);
      wg_fence();
#pragma unroll
      for (int k = 0; k < 12; k++) {
        wgmma_tt16(acc[k >> 2], cd.od[28 + k], cd.gd[8 + (k & 3)], 1);
        if ((k & 3) == 3) wg_commit();
      }
      __syncwarp();
      const uint32_t o = mo & ~3u;
      if (!S9E) { SEND(mo9, 3); __syncwarp(); }
      wg_wait<2>();
      SEND(o, 0);
      __syncwarp();
      wg_wait<1>();
      SEND((o ^ ((mo & 1) << 12)) + 8 * MAIL_UNIT, 1);
      __syncwarp();
      if (QGA == 2) bar_arrive(NB_GO, 256);
      wg_wait<0>();
      if (QGA == 3) bar_arrive(NB_GO, 256);
      TS(b, 30);
      if (PVE) bar_arrive(NB_V, 384);
      SEND((o ^ ((mo & 2) << 11)) + 16 * MAIL_UNIT, 2);
      if (!PVE) bar_arrive(NB_V, 384);
      if (QGA == 0) bar_arrive(NB_GO, 256);
#undef SEND
      TS(b, 9);
      arrive_all<BAR_RF>(peer, tid0 - 96);
      if (VD) { const uint32_t t0 = clk32(); while (clk32() - t0 < VD) {} }
    }
  }
  if (left <= 0) g_err = 2;
}

__device__ __forceinline__ uint4 add_msg(const uint4& a, const uint4& b) { return make_uint4(add_h2(a.x, b.x), add_h2(a.y, b.y), add_h2(a.z, b.z), add_h2(a.w, b.w)); }
__device__ __forceinline__ void publish(const ChainArgs& a, int b, int warp, uint32_t src, uint32_t off) {
  uint32_t v = SENT;
  if (warp < 2) {
    const float2 p = unpack_h2(lds32(src)), q = unpack_h2(lds32(src + 256)), r = unpack_h2(lds32(src + 512)), s = unpack_h2(lds32(src + 768));
    v = pack_bf16((p.x + q.x) + (r.x + s.x), (p.y + q.y) + (r.y + s.y));
    if (b + 1 == LAG && off >= 18432) v = ld_relaxed(a.mbuf + 2 * 40960 + off);
  }
  uint8_t* dst = a.mbuf + ((b + 1 + (warp >> 1)) & 1) * 40960 + off;
  st_relaxed(dst, v);
  st_relaxed(dst + 4096, v);
}
__device__ __forceinline__ void store_o(const ChainArgs& a, const uint4 (&ok)[4], int b, uint32_t off) {
  uint8_t* p = a.oimg + (b & 7) * (192 * 4096) + off;
  *reinterpret_cast<uint4*>(p) = ok[0]; *reinterpret_cast<uint4*>(p + 512) = ok[1];
  *reinterpret_cast<uint4*>(p + 96 * 4096) = ok[2]; *reinterpret_cast<uint4*>(p + 96 * 4096 + 512) = ok[3];
}

__device__ __forceinline__ void fetch_rows(const ChainArgs& a, uint32_t sb, int warp, int slot, uint32_t al) {
  using namespace C;
  const uint8_t* src = a.mbuf + slot * 40960;
  mbar_expect_tx(sb + BAR_M + 8 * warp, 5120);
  bulk_g2s(sb + OFF_R + warp * 4096, src + (warp * 8192 + ((al >> warp) & 1) * 4096), 4096, sb + BAR_M + 8 * warp);
  bulk_g2s(sb + OFF_R + 16384 + warp * 1024, src + (32768 + (al & 16) * 256 + warp * 1024), 1024, sb + BAR_M + 8 * warp);
}

__device__ __forceinline__ void wo_permute(uint4& u, uint4& v) {
  const uint4 e = make_uint4(__byte_perm(u.x, u.y, 0x5410), __byte_perm(u.z, u.w, 0x5410), __byte_perm(v.x, v.y, 0x5410), __byte_perm(v.z, v.w, 0x5410));
  v = make_uint4(__byte_perm(u.x, u.y, 0x7632), __byte_perm(u.z, u.w, 0x7632), __byte_perm(v.x, v.y, 0x7632), __byte_perm(v.z, v.w, 0x7632));
  u = e;
}

__device__ __forceinline__ void chain_a(const CUtensorMap& tmWq, const CUtensorMap& tmWk, const CUtensorMap& tmWv, const CUtensorMap& tmWo, const CUtensorMap& tmX,
                                        const ChainArgs& a, const uint32_t sb, const int tid0, const int cta, const int rank, const int unit, Counters* cnt) {
  using namespace C;
  asm volatile("setmaxnreg.dec.sync.aligned.u32 72;");
  int left = SPIN_BUDGET;
  const uint32_t peer = keep(mapa(sb, (tid0 & 3) % 3), tid0);
  const int warp = __shfl_sync(0xffffffffu, tid0 >> 5, 0);
  if (warp == 0) {
    const int col = (cta / 3) * DH + rank * 64;
#pragma unroll 1
    for (int i = 0; i < 16; i++) {
      if (i < 13) mbar_wait(sb + BAR_M + 8 * (i & 3), (i >> 2) & 1, left);
      if (tid0 == 0) {
        if (i == 9) mbar_arrive(sb + BAR_W1);
        if (i >= 13) mbar_arrive(sb + BAR_M + 8 * (i & 3));
        else if (i + WPF < 13) load_piece(tmWq, tmWk, tmWv, sb, col, i + WPF);
        else if (i + WPF < 15) { tma2d_prefetch(&tmWk, col, (i + WPF - 10) * 128); tma2d_prefetch(&tmWk, col, (i + WPF - 10) * 128 + 64); }
        else if (i + WPF == 15) for (int u = 2; u < 8; u++) tma2d_prefetch(&tmWo, wo_col(u, rank), wo_row(u, cta));
      }
      __syncwarp();
    }
  } else {
    if ((tid0 & 31) == 0) probe(a, sb, warp == 3 ? 5 : warp - 1, NT1, cta, unit, warp);
    __syncwarp();
    cnt_wait_warp(&cnt[CN_Z][0][32], 96, left);
  }
  PT2(3, 0); PT2(4, 32);
  bar_sync(NB_V, 384);
  uint32_t rsel;
  {
    const int lane = tid0 & 31;
    const uint2 t = lds64(sb + OFF_SEL + min(lane, 5) * 8);
    const uint32_t near = __ballot_sync(0xffffffffu, t.y < t.x), flip = ((near >> 1) ^ ((near & 1) * 15)) & 15;
    rsel = __ballot_sync(0xffffffffu, lane < 10 ? PL2 && ((near ^ __popc(lane & flip)) & 1) : PL1 && (((near >> 5) ^ __popc((lane - 10) & flip)) & 1)) & 0x3ffff;
  }
  cluster_sync_relaxed();
  arrive_all<BAR_RF>(peer, tid0);
  arrive_all<BAR_VF>(peer, tid0);
  fence_async_all();
  if (elect()) fetch_rows(a, sb, warp, 2, 0);
  __syncwarp();
  if (unit < NUNIT) {
#pragma unroll 1
    for (int i = tid0; i < (unit < 72 ? 1024 : 2048); i += 128)
      *reinterpret_cast<uint4*>(a.mail + (size_t)unit * MAIL_UNIT + (i >> 8) * 8192 + ((rsel >> (10 + (i >> 8))) & 1) * 4096 + (i & 255) * 16) = make_uint4(SENT, SENT, SENT, SENT);
  }
  bar_sync(NB_MR, 128);
  if (tid0 == 96) asm volatile("st.release.gpu.global.b32 [%0],%1;" ::"l"(&cnt[CN_S][0][0] + unit * 32), "r"(256 | (rsel >> 10)) : "memory");
  __syncwarp();
  mbar_wait(sb + BAR_RID, 0, left);
  mbar_wait(sb + BAR_M + 8 * warp, 0, left);
  bar_arrive(NB_M2, 256);
  TS(0, 0);
  mbar_wait(sb + BAR_W2, 0, left);
  mbar_wait(sb + BAR_W3, 0, left);
  PTS(6);
#pragma unroll 4
  for (int it = tid0; it < 1536; it += 128) {
    const int row = it >> 2, q = it & 3;
    const uint32_t a0 = sb + OFF_WO + row * 128 + (((2 * q) ^ (row & 7)) << 4), a1 = a0 ^ 16;
    uint4 u = lds128(a0), v = lds128(a1);
    wo_permute(u, v);
    sts128(a0, u);
    sts128(a1, v);
  }
  fence_async();
  uint32_t mph = 1;
  uint32_t mo = (unit < NUNIT ? unit : NUNIT) * MAIL_UNIT + warp * 8192 + ((rsel >> (10 + warp)) & 1) * 4096 + (tid0 & 31) * 16;
  const uint32_t mo2 = 32768 + (((rsel >> (10 + warp)) ^ (rsel >> (14 + warp))) & 1) * 4096;
  const bool up = warp >= 2, outer = warp == 0 || warp == 3;
  const uint32_t r1 = mapa(sb, (rank + 1) % 3), r2 = mapa(sb, (rank + 2) % 3);
  const uint32_t pa = keep_u(OFF_P + (2 * warp + (up ? 3 : 0)) * 768), ub = keep_u(xl_off(warp));
  const uint32_t ua = keep_u(outer ? pa : ub + 640), uc = keep_u(outer ? OFF_XM + (up ? 640 : 0) : ub + 640 + 3584);
  const uint32_t bx = keep_u(sb + BAR_X + (outer ? 0 : 8 + 8 * warp));
  const uint32_t l0 = keep((tid0 & 31) * 16, tid0);
  const uint32_t ka = keep(sb + OFF_KT + tile_lane(tid0) + ((tid0 & 16) ? 640 : 0), tid0);
  const uint32_t oo = keep(cta * 4096 + warp * 1024 + ((tid0 ^ ((tid0 >> 3) & 3)) & 31) * 16, tid0);
  uint32_t po;
  {
    const int lane = tid0 & 31;
    po = unit < 72 ? (warp & 1) * 10240 + unit * 128 + lane * 4
                   : (lane >> 4) * 10240 + (36 + (unit >> 1)) * 128 + (lane & 3) * 32 + (lane & 8) * 2 + (unit & 1) * 8 + (lane & 4);
    po = keep((po >> 12) * 8192 + (po & 4095) + ((unit < 72 ? (warp & 1) * 128 + (lane & 3) * 32 + (lane & 28) : lane * 8 + ((lane >> 1) & 4)) << 24), tid0);
  }
  uint4 ok[4] = {};
  bool xok = false;
  DUR(1);
  __syncwarp();

  for (int b = 0; b < NS; b++) {
    const int ph = b & 1;
    {
      float d[16];
      bar_sync(NB_MR, 128);
      wg_fence();
#pragma unroll
      for (int k = 0; k < 40; k++) {
        wgmma_ts32(d, cd.kd[k], RD(k), k);
        if (k == OSK) {
          __syncwarp();
          store_o(a, ok, b - 1, fresh(oo));
          __syncwarp();
          asm volatile("{.reg .pred p; setp.eq.u32 p,%1,0; @p mbarrier.arrive.shared::cta.b64 _,[%0];}" ::"r"(sb + BAR_OS), "r"(l0) : "memory");
        }
      }
      wg_commit();
      TS_FLUSH(b - 1);
      mbar_wait(sb + BAR_XE, ph, left);
      wg_wait<0>();
      if (VE) bar_arrive(NB_M, 256);
      TS(b, 25);
      store_pair(d, 0, 1, ka);
      store_pair(d, 2, 3, ka + 4 * 128);
      fence_async();
    }
    {
      const uint32_t l16 = fresh(l0), l4 = (l16 >> 2) + 512;
      float x0[20], x1[20];
      bar_sync(NB_QK, 384);
      TSB(b, 1);
      wg_fence();
#pragma unroll
      for (int kk = 0; kk < 4; kk++) {
        wgmma_tt40(x0, cd.sd[4 * kk], cd.sd[4 * kk + 1], kk);
        wgmma_tt40(x1, cd.sd[4 * kk + 2], cd.sd[4 * kk + 3], kk);
      }
      wg_commit();
      wg_wait<0>();
      bar_arrive(NB_S, 288);
      TS(b, 2);
      uint32_t h[5], z[5];
#pragma unroll
      for (int j = 0; j < 5; j++) h[j] = pack_h2(up ? x1[4 * j + 2] : x0[4 * j], up ? x1[4 * j + 3] : x0[4 * j + 1]);
      if (outer) {
        st_async4(r1 + uc + l16, h[0], h[1], h[2], h[3], r1 + BAR_X);
        st_async4(r2 + ua + l16, h[0], h[1], h[2], h[3], r2 + BAR_X);
        st_async1(r1 + uc + l4, h[4], r1 + BAR_X);
        st_async1(r2 + ua + l4, h[4], r2 + BAR_X);
      } else {
        sts128(sb + ua + 7168 + l16, make_uint4(h[0], h[1], h[2], h[3]));
      }
#pragma unroll
      for (int j = 0; j < 5; j++) z[j] = pack_h2(up ? x1[4 * j] : x0[4 * j + 2], up ? x1[4 * j + 1] : x0[4 * j + 3]);
      if (!outer) {
#pragma unroll
        for (int j = 0; j < 2; j++) z[3 + j] = pack_h2(up ? x0[4 * j] : x1[4 * j + 2], up ? x0[4 * j + 1] : x1[4 * j + 3]);
        h[3] = add_h2(h[3], diag_mask(l16 >> 4));
      }
      sts128(sb + ub + 7168 + l16, make_uint4(z[0], z[1], z[2], z[3]));
      sts32(sb + ub + 7168 + l4, z[4]);
      bar_arrive(NB_X + warp, 64);
      TS(b, 3);
      mbar_wait(bx, ph, left);
      TS(b, 4);
      {
        const uint4 u = lds128(sb + ua + l16), v = lds128(sb + uc + l16);
        const uint32_t tu = lds32(sb + ua + l4), tv = lds32(sb + uc + l4);
        h[0] = add_h2(add_h2(h[0], u.x), v.x); h[1] = add_h2(add_h2(h[1], u.y), v.y); h[2] = add_h2(add_h2(h[2], u.z), v.z);
        h[3] = add_h2(add_h2(h[3], u.w), v.w); h[4] = outer ? add_h2(add_h2(h[4], tu), tv) : 0xFC00FC00u;
        const float2 mf = unpack_h2(quad_max_h2(max_h2(max_h2(max_h2(h[0], h[1]), max_h2(h[2], h[3])), h[4])));
        const float m = -SCL * fmaxf(mf.x, mf.y);
        float y[10];
#pragma unroll
        for (int j = 0; j < 5; j++) { const float2 f = unpack_h2(h[j]); y[2 * j] = ex2(fmaf(f.x, SCL, m)); y[2 * j + 1] = ex2(fmaf(f.y, SCL, m)); }
        const float sum = ((y[0] + y[1]) + (y[2] + y[3])) + ((y[4] + y[5]) + (y[6] + y[7])) + (y[8] + y[9]);
        if (DN && outer) {
          p_store(sb + pa + l16, pack_bf16(y[0], y[1]), pack_bf16(y[2], y[3]), pack_bf16(y[4], y[5]), pack_bf16(y[6], y[7]), pack_bf16(y[8], y[9]));
          fence_async();
          bar_arrive(NB_P, 192);
          sts32(sb + OFF_INV + (up ? 32 : 0) + ((l16 >> 4) & 28), __float_as_uint(rcp(quad_sum(sum))));
          if (b + 1 < NS) bar_arrive(NB_P2, 192);
        } else {
          const float r = rcp(quad_sum(sum));
          p_store(sb + pa + l16, pack_bf16(y[0] * r, y[1] * r), pack_bf16(y[2] * r, y[3] * r), pack_bf16(y[4] * r, y[5] * r),
                  pack_bf16(y[6] * r, y[7] * r), pack_bf16(y[8] * r, y[9] * r));
          fence_async();
          if (!DN && outer) bar_arrive(NB_P, 192);
        }
      }
      TS(b, 5);
    }
    const int bn = b + 1;
    if (warp == 0 && bn < NS) {
      if (!NOX && bn >= LAG && !xok) {
        cnt_wait_warp(&cnt[CN_X][bn - LAG][0], 4, left);
        fence_async_all();
      }
      mbar_wait(sb + BAR_OE, ph, left);
      if (elect()) load_chunk(tmX, sb, bn, rank, slot_off(0) + rank * SLOT, BAR_F0);
      TS(b, 20);
      mbar_wait(sb + BAR_RQ, ph, left);
      if (elect()) load_chunk(tmX, sb, bn, 3 + rank, slot_off(3) + rank * SLOT, BAR_F1);
      __syncwarp();
    }
    if (warp == 3 && bn < NS) {
      mbar_wait(sb + BAR_ROT, ph, left);
      mbar_wait(sb + BAR_OE, ph, left);
      bar_sync(NB_O, 160);
      if (elect()) {
        bulk_s2c(r1 + OFF_OG + 2048, sb + OFF_OG, 2048, r1 + BAR_OG);
        bulk_s2c(r2 + OFF_OG + 4096, sb + OFF_OG, 2048, r2 + BAR_OG2);
      }
      __syncwarp();
    }
    uint4 x[6];
    uint32_t tf = 0;
    bar_sync(NB_V, 384);
    {
      float o0[16], o1[16];
      wg_fence();
#pragma unroll
      for (int q = 0; q < 3; q++) {
        wgmma_ss32(o0, cd.vd[q], cd.pd[6 + q], q);
        wgmma_ss32(o1, cd.vd[3 + q], cd.pd[9 + q], q);
      }
      wg_commit();
      if (bn < NS) {
        if (unit < 72) mbar_wait(sb + BAR_RF, ph ^ 1, left);
        if (QGA == 1) bar_arrive(NB_GO, 256);
        tf = clk32();
        if (B1 && unit < 72 && (unit >> 3) % 3 >= B1T) while (clk32() - tf < B1) {}
      }
      ld_msg16x4(x, a.mail + mo);
      __syncwarp();
      wg_wait<0>();
      if (warp == 2) arrive_all<BAR_VF>(mapa(sb, (fresh(l0) >> 4) & 3), l0 >> 4);
#pragma unroll
      for (int h = 0; h < 2; h++) {
        ok[h] = make_uint4(pack_bf16(o0[12 + 2 * h], o0[13 + 2 * h]), pack_bf16(o0[8 + 2 * h], o0[9 + 2 * h]),
                           pack_bf16(o0[4 + 2 * h], o0[5 + 2 * h]), pack_bf16(o0[2 * h], o0[1 + 2 * h]));
        ok[2 + h] = make_uint4(pack_bf16(o1[2 * h], o1[1 + 2 * h]), pack_bf16(o1[4 + 2 * h], o1[5 + 2 * h]),
                               pack_bf16(o1[8 + 2 * h], o1[9 + 2 * h]), pack_bf16(o1[12 + 2 * h], o1[13 + 2 * h]));
      }
      TS(b, 28);
    }
    if (bn < NS) {
      const int lane = fresh(l0) >> 4;
      const uint32_t tag = (b >> 1) & 1;
      int n = 1;
      if (unit < NUNIT) {
        const bool big = unit >= 72;
        if (big) ld_msg16x2(x + 4, a.mail + (mo ^ mo2));
        else x[4] = x[5] = make_uint4(tag, 0, 0, 0);
        __syncwarp();
#pragma unroll 1
        while (__any_sync(0xffffffffu, (differ4(x[0].x, x[1].x, x[2].x, x[3].x, tag) | differ4(x[4].x, x[5].x, x[4].x, x[5].x, tag)) & 1) && (left -= 16) > 0) {
          ld_msg16x4(x, a.mail + mo);
          if (big) ld_msg16x2(x + 4, a.mail + (mo ^ mo2));
          __syncwarp();
          n++;
        }
        TS(b, 10);
        TSV(b, 15, n);
        uint4 e = add_msg(add_msg(x[0], x[1]), add_msg(x[2], x[3]));
        if (big) e = add_msg(e, add_msg(x[4], x[5]));
        const bool b4 = lane & 16;
        uint32_t f0 = add_h2(b4 ? e.z : e.x, __shfl_xor_sync(0xffffffffu, b4 ? e.x : e.z, 16));
        uint32_t f1 = add_h2(b4 ? e.w : e.y, __shfl_xor_sync(0xffffffffu, b4 ? e.y : e.w, 16));
        if (big) { f0 = add_h2(f0, __shfl_xor_sync(0xffffffffu, f0, 8)); f1 = add_h2(f1, __shfl_xor_sync(0xffffffffu, f1, 8)); }
        asm volatile("st.shared.v2.b32 [%0],{%1,%2};" ::"r"(sb + OFF_SCR + warp * 256 + lane * 8), "r"(f0), "r"(f1) : "memory");
        bar_sync(NB_MR, 128);
        const uint32_t p = fresh(po);
        if (!(big && (warp & 1))) publish(a, b, warp, sb + OFF_SCR + (p >> 24), p & 0xFFFF);
      }
      tf = max((int)(clk32() - tf) + B2, B3) + tf;
      mo ^= 2048;
      TS(b, 11);
      if (!NOX && warp == 0 && bn + 1 >= LAG) {
        xok = __all_sync(0xffffffffu, ld_acquire(&cnt[CN_X][bn + 1 - LAG][0]) >= 4);
        fence_async_all();
      }
      if (rank < 2) {
        const int q = 2 * rank + (warp >> 1), blk = (warp & 1) ? 4 : q, o = blk * 4096 + ((warp & 1) ? q * 1024 : 0);
        const uint8_t* src = a.mbuf + (uint32_t)((ph ^ 1) * 40960 + o + (blk + ((rsel >> (5 - 5 * ph + blk)) & 1)) * 4096);
        while ((int)(clk32() - tf) < 0) {}
        if (elect()) bulk_g2s_mc(sb + OFF_R + o, src, (warp & 1) ? 1024 : 4096, sb + BAR_M + 8 * q);
        __syncwarp();
      }
      TS(b + 1, 12);
    }
    if (bn < NS) {
      const uint32_t l16 = fresh(l0), va = sb + OFF_R + l16 * 2 + ((l16 >> 4) & 28);
      int n = 0;
      mbar_wait(sb + BAR_RID, ph ^ 1, left);
#pragma unroll 1
      while (true) {
        mbar_wait(sb + BAR_M + 8 * warp, mph, left);
        if (n == 0) TS(bn, 13);
        const uint32_t v0 = lds32(va + warp * 4096), v1 = lds32(va + warp * 4096 + 1024), v2 = lds32(va + warp * 4096 + 2048), v3 = lds32(va + warp * 4096 + 3072);
        const uint32_t v4 = lds32(va + 16384 + warp * 1024), v5 = lds32((va ^ 8) + (warp == 2 ? 9216 : 16384 + warp * 1024));
        mph ^= 1;
        n++;
        if (!__any_sync(0xffffffffu, max(max(max(v0, v1), v2), max(max(v3, v4), v5)) == SENT) || (left -= 16) <= 0) break;
        const uint32_t al = keep_u(rsel) >> (5 - 5 * ph);
        if (elect()) fetch_rows(a, sb, warp, ph ^ 1, al);
        __syncwarp();
      }
      bar_arrive(NB_M2, 256);
      TS(bn, 0);
      TSV(bn, 14, n);
    }
  }
  store_o(a, ok, NS - 1, oo);
  bar_sync(NB_MR, 128);
  if (tid0 == 0) cnt_signal(&cnt[CN_O][NS - 1][(cta >> 4) * 32]);
  TS_FLUSH(NS - 1);
  if (left <= 0) g_err = 3;
}

#define XF 1
#define NT2 4
__global__ void __cluster_dims__(3, 1, 1) __launch_bounds__(384, 1)
k_chain(const __grid_constant__ ChainArgs args, const __grid_constant__ CUtensorMap tmWq, const __grid_constant__ CUtensorMap tmWk, const __grid_constant__ CUtensorMap tmWv,
        const __grid_constant__ CUtensorMap tmWo, const __grid_constant__ CUtensorMap tmX) {
  using namespace C;
  extern __shared__ __align__(1024) uint8_t smem[];
  const uint32_t sb = smem_u32(smem);
  const int tid = threadIdx.x;
  const int wg = __shfl_sync(0xffffffffu, tid >> 7, 0);
  const int cta = blockIdx.x, rank = cta % 3;
  DUR(0);
  asm volatile("griddepcontrol.launch_dependents;");
  if (tid == 0) {
    if ((sb & 0xFFFFFF) != SB0) g_err = 100;
    for (int i = 0; i < 19; i++) mbar_init(sb + OFF_BAR + 8 * i, 1);
    mbar_init(sb + BAR_XE, 6); mbar_init(sb + BAR_OE, 3); mbar_init(sb + BAR_RQ, 3); mbar_init(sb + BAR_VF, 3); mbar_init(sb + BAR_RF, 3);
    mbar_init(sb + BAR_RE, 6); mbar_init(sb + BAR_OS, 4);
    asm volatile("fence.mbarrier_init.release.cluster;" ::: "memory");
    fence_async();
    if (!XF) for (int i = 0; i < WPF; i++) load_piece(tmWq, tmWk, tmWv, sb, (cta / 3) * DH + rank * 64, i);
  }
  if (tid >= 32 && tid < 44) sts32(sb + OFF_SEL + (tid - 32) * 4, SENT);
  const uint32_t launch = ld_relaxed(&g_launch);
  const int unit = rank < 2 ? (cta / 3) * 2 + rank : 64 + cta / 3;
  if (wg) {
    const int warp = tid >> 5, lane = tid & 31;
    uint4 v[3][3], e[4], f[4];
#pragma unroll
    for (int i = 0; i < 3; i++) ln_row_load(args.x0, v[i], min(cta + 96 * i, 255) * 8 + warp - 4, lane);
#pragma unroll
    for (int i = 0; i < 4; i++) {
      const int u = i < 2 ? i : i + 6;
      const uint4* src = reinterpret_cast<const uint4*>(args.wo + (size_t)(wo_row(u, cta) + ((tid - 128) >> 2)) * DM + wo_col(u, rank) + (tid & 3) * 16);
      e[i] = ld_nc16(src); f[i] = ld_nc16(src + 1);
    }
    __syncthreads();
    if (tid < 128 + 80) {
      const int j = cta * 80 + tid - 128, i = j % 2560, p = ((i >> 9) * 256 + (i & 255)) % 640;
      reinterpret_cast<uint4*>(args.mbuf)[j] = j < 5120 ? make_uint4(SENT, SENT, SENT, SENT) : ld_nc16(args.mem0 + (p & 7) * DM + (p >> 3) * 8);
    }
#pragma unroll
    for (int i = 0; i < 3; i++) ln_row(v[i], lane);
    uint4* st = reinterpret_cast<uint4*>(smem + STAGE_X);
#pragma unroll
    for (int i = 0; i < 3; i++) {
      const int g = cta + 96 * i;
      if (g < 256) {
#pragma unroll
        for (int j = 0; j < 3; j++)
          if (j < 2 || lane < 16) st[(lane + 32 * j) * 8 + (((warp - 4) ^ lane) & 7)] = v[i][j];
        bar_sync(NB_BQ, 256);
        for (int j = tid - 128; j < 640; j += 256) reinterpret_cast<uint4*>(args.xn)[g * 640 + j] = st[(j & ~7) | ((j ^ (j >> 3)) & 7)];
        bar_sync(NB_BQ, 256);
      }
    }
    PT2(0, 128);
    if (warp == 11) {
      if (lane == 0) cnt_signal(&g_cnt[launch & 1][CN_Z][0][32]);
      if (cta * 32 + lane < 7 * (NS + 1) * 6) (&g_cnt[~launch & 1][0][0][0])[(cta * 32 + lane) * 32] = 0;
      static_assert(7 * (NS + 1) * 6 <= 96 * 32, "counters");
    } else if (lane == 0 && warp != 7) probe(args, sb, 2 + (warp & 3), NT2, cta, unit, warp);
    __syncwarp();
    PT2(1, 128);
    bar_arrive(NB_V, 384);
#pragma unroll
    for (int i = 0; i < 4; i++) {
      const int row = (tid - 128) >> 2;
      wo_permute(e[i], f[i]);
      const uint32_t o = i * 8192 + row * 128 + (((2 * (tid & 3)) ^ (row & 7)) << 4);
      *reinterpret_cast<uint4*>(args.rot + (size_t)cta * 32768 + o) = e[i];
      *reinterpret_cast<uint4*>(args.rot + (size_t)cta * 32768 + (o ^ 16)) = f[i];
    }
  } else {
    __syncthreads();
    if (XF && tid == 0) for (int i = 0; i < WPF; i++) load_piece(tmWq, tmWk, tmWv, sb, (cta / 3) * DH + rank * 64, i);
    __syncwarp();
  }
  Counters* cnt = args.cnt + 7 * __shfl_sync(0xffffffffu, launch & 1, 0);

  if (wg == 0) chain_a(tmWq, tmWk, tmWv, tmWo, tmX, args, sb, own_tid(), cta, rank, unit, cnt);
  else if (wg == 1) chain_q(tmWk, tmWo, tmX, args, sb, own_tid(), cta, rank, cnt);
  else chain_v(args, sb, own_tid(), cta, rank, cnt);
  DUR(2);
  cluster_sync();
}

#define WDL 1
#define PRE 0
#define HD 0
namespace W {
constexpr int NW = 36, NP = 30, OW0 = 31;
#define BIGG 0
constexpr int QST = BIGG ? 3 : 4;
constexpr int QK = 4 * QST - 2, QR = BIGG ? 4 : 3;
constexpr int GST = BIGG ? 6 : 4;
constexpr int OFF_WS = 0;
constexpr int OFF_WQ = 94208;
constexpr int OFF_G = 176128;
constexpr int OFF_GO = 8192;
constexpr int OFF_Q = OFF_G + (BIGG ? 32768 : 24576);
constexpr int PITCH = 144;
constexpr int OFF_STG = OFF_Q + (QST - 2) * 8192;
constexpr int OFF_HIST = OFF_Q + QK * 2048;
constexpr int OFF_ST = OFF_HIST + 2240;
constexpr int OFF_BAR = OFF_ST + 256;
constexpr int SMEM = OFF_BAR + 288;
constexpr int BAR_GF = OFF_BAR, BAR_GE = OFF_BAR + 64, BAR_QF = OFF_BAR + 128, BAR_QE = OFF_BAR + 184, BAR_W1 = OFF_BAR + 240, BAR_W2 = OFF_BAR + 248,
              BAR_H = OFF_BAR + 256;
constexpr int NB_PRO = 1, NB_Q = 2, NB_L = 3, NB_L2 = 4, NB_A = 5;
constexpr uint32_t sb = C::SB0;
static_assert(SMEM <= 232448, "shared memory");
template <bool IS_O> __host__ __device__ constexpr bool in_smem(int k) { return IS_O ? k == 39 : (k & 7) == 2 || (k & 7) == 4 || ((k & 7) == 7 && k != 63); }
template <bool IS_O> __host__ __device__ constexpr int smem_before(int k) { return IS_O ? 0 : 3 * (k >> 3) + ((k & 7) > 2) + ((k & 7) > 4); }
template <bool IS_O> __host__ __device__ constexpr int chunk_k(int c) { return IS_O ? 5 * c : BIGG ? 32 * (c / 6) + 5 * (c % 6) + (c % 6 < 2 ? c % 6 : 2) : c < 4 ? 6 * c : 4 + 5 * c; }
template <bool IS_O> __host__ __device__ constexpr int stage_off(int c) { return IS_O ? OFF_GO + c * 5120 : BIGG ? OFF_G + chunk_k<false>(c % 6) * 1024 : OFF_G + (c & 3) * 6144; }
}

struct WorkArgs {
  const bf16* x0;
  bf16* out;
  const bf16* wqkv;
  uint64_t pd[32], od[40], qw[80];
};
static void fill_descs(WorkArgs& a) {
  using namespace W;
  for (int k = 0; k < 32; k++) a.pd[k] = mkdesc64(sb + OFF_G + k * 1024, 512, 512);
  for (int k = 0; k < 40; k++) {
    a.qw[2 * k] = mkdesc(sb + OFF_WQ + k * 2048, 8192, 1024);
    a.qw[2 * k + 1] = mkdesc64(sb + OFF_Q + ((k % QK) >> 1) * 4096 + (k & 1) * 32, 16, 512);
  }
  for (int k = 0; k < 40; k++) a.od[k] = mkdesc_ns(sb + OFF_GO + k * 1024, 512, 128);
}
__device__ __forceinline__ void pass_wait(uint32_t target, int& left) {
  uint32_t v;
  do {
    asm volatile("ld.acquire.cta.shared.u32 %0,[%1];" : "=r"(v) : "r"(W::sb + W::BAR_H) : "memory");
    if (!__any_sync(0xffffffffu, v < target)) break;
    __nanosleep(30);
  } while (--left > 0);
}
__device__ __forceinline__ const uint8_t* opaque(const uint8_t* p) {
  return reinterpret_cast<const uint8_t*>(__shfl_sync(0xffffffffu, reinterpret_cast<unsigned long long>(p), 0));
}
__device__ __forceinline__ uint4 ld_relaxed16(const void* p) {
  uint4 v; asm volatile("ld.relaxed.gpu.global.v4.u32 {%0,%1,%2,%3},[%4];" : "=r"(v.x), "=r"(v.y), "=r"(v.z), "=r"(v.w) : "l"(p) : "memory"); return v;
}
__device__ __forceinline__ uint4 ld_msg8x2(const void* p) {
  uint4 v;
  asm volatile("{.reg .b64 a,b; ld.relaxed.gpu.global.v2.b64 {a,b},[%4]; mov.b64 {%0,%1},a; mov.b64 {%2,%3},b;}" : "=r"(v.x), "=r"(v.y), "=r"(v.z), "=r"(v.w) : "l"(p) : "memory");
  return v;
}
__device__ __forceinline__ void st_msg8(void* p, uint32_t x, uint32_t y) {
  asm volatile("{.reg .b64 r; mov.b64 r,{%1,%2}; st.relaxed.gpu.global.b64 [%0],r;}" ::"l"(p), "r"(x), "r"(y) : "memory");
}
template <bool LATE>
__device__ __forceinline__ bool job_of(int n, int& l, int& s) {
  const int i = n >> 1, j = n & 1;
  l = j; s = i - j * (LAG + LATE);
  return s >= 0 && s < NSEG;
}

template <bool IS_O>
__device__ __forceinline__ void work_g_weights(const CUtensorMap& tm, int w, int warp, bool second) {
  using namespace W;
  constexpr int NK = IS_O ? 40 : 64;
  const int col = (IS_O ? w - OW0 : w % 5) * 128, row = IS_O ? 0 : (w / 5) * 1024;
  int ns = 0;
#pragma unroll 1
  for (int k = 0; k < NK; k++) {
    const bool s = in_smem<IS_O>(k);
    if (s == second && (k & 1) == (warp & 1)) {
      const int t = warp >> 1;
      tma2d(sb + (s ? OFF_WS + (t * (IS_O ? 1 : 23) + ns) * 2048 : (t * 41 + k - ns) * 2048), &tm, col + t * 64, row + k * 16, sb + (s ? BAR_W2 : BAR_W1));
    }
    ns += s;
  }
}

template <bool IS_O>
__device__ __forceinline__ void work_g_producer(int w, Counters* cnt) {
  using namespace W;
  constexpr int NC = IS_O ? 8 : 12;
  int left = SPIN_BUDGET;
  uint32_t ph = 1;
#pragma unroll 1
  for (int i = 0; i < NS + IS_O; i++) {
    if (NOX && !IS_O && i >= LAG - 1 && i - LAG + 1 < NSEG) cnt_wait_warp(&cnt[CN_X][i - LAG + 1][0], 4, left);
    if (!IS_O) {
      cnt_wait_warp(&cnt[CN_O][i][(w / 5) * 32], 16, left);
      if (w == WW) WTS(i, 0);
      fence_async_all();
    }
#pragma unroll 1
    for (int j = 0; j < 2; j++) {
      int l, s;
      if (!job_of<IS_O>(2 * i + j, l, s)) continue;
      if (IS_O) {
        cnt_wait_warp(&cnt[CN_A][s][l * 32], 32, left);
        if (w == 35 && (l == 0 || i >= NSEG)) WTS(i, 8);
        fence_async_all();
      }
      const uint8_t* src = opaque(IS_O ? g_ob[s & 7][l] : g_o[i & 7][l][(w / 5) * 16]);
      constexpr int NB = IS_O ? 4 : GST;
#pragma unroll 1
      for (int r = 0; r < NC / NB; r++) {
        const int s0 = IS_O ? 4 * r : 0;
#pragma unroll
        for (int c = 0; c < NB; c++) {
          const int n = IS_O ? 5120 : BIGG ? (c < 2 ? 6144 : 5120) : r == 0 ? 6144 : 5120;
          mbar_wait(sb + BAR_GE + 8 * (s0 + c), ph, left);
          if (elect()) {
            mbar_expect_tx(sb + BAR_GF + 8 * (s0 + c), n);
            bulk_g2s(sb + stage_off<IS_O>(c) + s0 * 5120, src, n, sb + BAR_GF + 8 * (s0 + c));
          }
          src += n;
        }
        if (!IS_O || r) ph ^= 1;
      }
    }
  }
}

__device__ __forceinline__ uint32_t add_bf2(uint32_t a, uint32_t b) { uint32_t r; asm("add.rn.bf16x2 %0,%1,%2;" : "=r"(r) : "r"(a), "r"(b)); return r; }
template <int N, int LOW>
__device__ __forceinline__ void merge_stats(float m0, float m1, float q0, float q1, float& m, float& q, int lane) {
  const bool up = lane & 16;
  m = up ? m1 : m0; q = up ? q1 : q0;
  float n = 0.5f * N;
#pragma unroll
  for (int o = 16; o >= LOW; o >>= 1) {
    const float mo = __shfl_xor_sync(0xffffffffu, o < 16 ? m : up ? m0 : m1, o), qo = __shfl_xor_sync(0xffffffffu, o < 16 ? q : up ? q0 : q1, o);
    const float d = mo - m;
    m = fmaf(0.5f, d, m); q = fmaf(n * d, d, q + qo);
    n *= 2.f;
  }
}
template <int LOW>
__device__ __forceinline__ void pair_stats(const uint32_t (&x)[20], float& m, float& q, int lane) {
  float m0 = 0.f, m1 = 0.f, q0 = 0.f, q1 = 0.f;
#pragma unroll
  for (int j = 0; j < 20; j++) {
    const float e = bf_lo(x[j]), f = bf_hi(x[j]);
    m0 += e; m1 += f; q0 = fmaf(e, e, q0); q1 = fmaf(f, f, q1);
  }
  merge_stats<20, LOW>(m0 * 0.05f, m1 * 0.05f, fmaxf(fmaf(m0 * -0.05f, m0, q0), 0.f), fmaxf(fmaf(m1 * -0.05f, m1, q1), 0.f), m, q, lane);
}
__device__ __forceinline__ void add_product(uint32_t (&r)[20], const uint4 (&x)[5]) {
#pragma unroll
  for (int n = 0; n < 20; n++) {
    const uint4& v = x[n >> 2];
    const float2 f = unpack_h2((n & 3) == 0 ? v.x : (n & 3) == 1 ? v.y : (n & 3) == 2 ? v.z : v.w);
    r[n] = add_bf2(r[n], pack_bf16(f.x, f.y));
  }
}
__device__ __forceinline__ void load20(uint32_t (&r)[20], const uint8_t* p, int stride) {
#pragma unroll
  for (int m = 0; m < 5; m++) { const uint4 u = ld_relaxed16(p + m * stride); r[4 * m] = u.x; r[4 * m + 1] = u.y; r[4 * m + 2] = u.z; r[4 * m + 3] = u.w; }
}
__device__ __forceinline__ void poll5(uint4 (&x)[5], const uint8_t* src, int stride, uint32_t tag, int& left) {
#pragma unroll 1
  while (true) {
#pragma unroll
    for (int j = 0; j < 5; j++) x[j] = ld_msg8x2(src + j * stride);
    __syncwarp();
    const uint32_t bad = differ4(x[0].x, x[0].z, x[1].x, x[1].z, tag) | differ4(x[2].x, x[2].z, x[3].x, x[3].z, tag) | differ4(x[4].x, x[4].z, x[4].x, x[4].z, tag);
    if (!__any_sync(0xffffffffu, bad & 1) || (left -= 16) <= 0) break;
  }
}
__device__ __forceinline__ uint32_t norm_lo(uint32_t a, uint32_t b, float q, float m) { return pack_bf16(fmaf(bf_lo(a), q, m), fmaf(bf_lo(b), q, m)); }
__device__ __forceinline__ uint32_t norm_hi(uint32_t a, uint32_t b, float q, float m) { return pack_bf16(fmaf(bf_hi(a), q, m), fmaf(bf_hi(b), q, m)); }
__device__ __forceinline__ float part_var(float mp, float q, float n, float m) { const float d = mp - m; return fmaf(n * d, d, q); }
#define F(x) __uint_as_float(x)

__device__ __forceinline__ void work_l(const WorkArgs& a, int lane0, int p, int mask, Counters* cnt) {
  using namespace W;
  int left = SPIN_BUDGET, n = mask == 2 ? 2 * LAG + 1 : 0, nl = mask == 2, ns = 0;
  bool ready = false;
#pragma unroll 1
  while (n < 2 * NS) {
    const int l = nl, s = ns, round = (n + 1) >> 1;
    do n++; while (n < 2 * NS && !(job_of<false>(n, nl, ns) && ((mask >> nl) & 1)));
    if (!ready) cnt_wait_warp(&cnt[CN_P][s][l * 32], NP, left);
    if (p == 5 && lane0 == 0 && (l == 0 || round >= NSEG)) WTS(round, 14);
    int lane = fresh(lane0);
    uint32_t r[20];
    const uint32_t ao = (p & 3) * 10240 + (p >> 2) * 64 + (lane >> 2) * 256 + (lane & 3) * 16;
    {
      uint4 x[5];
      const uint8_t* acc = g_part[s % MD][l] + ao;
#pragma unroll
      for (int m = 0; m < 5; m++) x[m] = ld_relaxed16(acc + m * 2048);
      if (l) {
        load20(r, g_xs[1] + (uint32_t)((s * 4 + (p >> 2)) * 10240 + (p & 3) * 16 + lane * 64), 2048);
      } else {
        const uint2* q = reinterpret_cast<const uint2*>(a.x0) + (uint32_t)((s * 16 + p) * 320 + lane);
#pragma unroll
        for (int m = 0; m < 5; m++)
          asm volatile("ld.global.nc.v2.u32 {%0,%2},[%4]; ld.global.nc.v2.u32 {%1,%3},[%4+1280];"
                       : "=r"(r[4 * m]), "=r"(r[4 * m + 1]), "=r"(r[4 * m + 2]), "=r"(r[4 * m + 3]) : "l"(q + m * 32));
        __syncwarp();
#pragma unroll
        for (int j = 0; j < 20; j += 2) { const uint32_t u = r[j]; r[j] = __byte_perm(u, r[j + 1], 0x5410); r[j + 1] = __byte_perm(u, r[j + 1], 0x7632); }
      }
      __syncwarp();
      add_product(r, x);
    }
    __syncwarp();
    lane = fresh(lane0);
    uint8_t* xp = g_xs[2 * l] + (uint32_t)((s * 16 + p) * 2560 + lane * 16);
#pragma unroll
    for (int m = 0; m < 5; m++) *reinterpret_cast<uint4*>(xp + m * 512) = make_uint4(r[4 * m], r[4 * m + 1], r[4 * m + 2], r[4 * m + 3]);
    const uint32_t peek = ld_relaxed(&cnt[CN_P][min(ns, NSEG)][nl * 32]);
    float m, q;
    pair_stats<1>(r, m, q, lane);
    q = rsqrtf(q * (1.f / DM) + 1e-5f);
    m *= -q;
    const float q0 = __shfl_sync(0xffffffffu, q, 0), q1 = __shfl_sync(0xffffffffu, q, 16);
    const float m0 = __shfl_sync(0xffffffffu, m, 0), m1 = __shfl_sync(0xffffffffu, m, 16);
    uint8_t* img = g_xnb[round & 7] + (uint32_t)((lane >> 3) * 4096 + (l * 16 + p) * 128 + (((lane & 7) ^ ((p & 3) << 1)) << 3));
#pragma unroll
    for (int j = 0; j < 20; j += 4) {
      __syncwarp();
      *reinterpret_cast<uint2*>(img + j * 4096) = make_uint2(norm_lo(r[j], r[j + 1], q0, m0), norm_lo(r[j + 2], r[j + 3], q0, m0));
      *reinterpret_cast<uint2*>(img + j * 4096 + 64) = make_uint2(norm_hi(r[j], r[j + 1], q1, m1), norm_hi(r[j + 2], r[j + 3], q1, m1));
    }
    __syncwarp();
    if (p == 5 && lane == 0 && (l == 0 || round >= NSEG)) WTS(round, 4);
    ready = __all_sync(0xffffffffu, peek >= NP);
    asm volatile("fence.acq_rel.gpu;" ::: "memory");
    if (elect()) asm volatile("red.relaxed.gpu.global.add.u32 [%0],1;" ::"l"(&cnt[CN_L][round][0]) : "memory");
    __syncwarp();
    uint8_t* acc = g_part[s % MD][l] + ao;
#pragma unroll
    for (int m = 0; m < 5; m++) *reinterpret_cast<uint4*>(acc + m * 2048) = make_uint4(0, 0, 0, 0);
  }
  if (left <= 0) g_err = 14;
}

template <bool IS_O>
__device__ __forceinline__ void work_g(const WorkArgs& a, int w, int tile, int tid0, Counters* cnt) {
  using namespace W;
  constexpr int NC = IS_O ? 8 : 12, NST = IS_O ? 8 : GST;
  int left = SPIN_BUDGET;
  uint32_t ph = 0;
  constexpr int NR = IS_O ? 39 : 41;
  uint32_t wf[NR][4];
  mbar_wait(sb + BAR_W1, 0, left);
  load_wfrags<NR>(wf, sb + tile * 41 * 2048, tid0 >> 5, tid0 & 31);
  bar_sync(NB_PRO, 512);
  mbar_wait(sb + BAR_W2, 0, left);
  cnt_wait_warp(&cnt[CN_Z][0][0], NW, left);
  const uint32_t wlo = (uint32_t)mkdesc(C::SB0 + OFF_WS, 8192, 1024) + tile * (IS_O ? 128 : 23 * 128);
  constexpr uint32_t WHI = (uint32_t)(mkdesc(0, 8192, 1024) >> 32);
  const int g = (tid0 & 31) >> 2, t = tid0 & 3;
  const int col = (IS_O ? w - OW0 : w % 5) * 128 + tile * 64 + (tid0 >> 5) * 16 + ((g & 1) ? g + 7 : g);
  const uint32_t mo = (col >> 4) * 256 + t * 64 + (col & 15) * 4, mo0 = IS_O ? (col >> 2) * 64 + t * 16 + (col & 3) * 4 : mo;
#pragma unroll 1
  for (int il = 0; il < 2 * (NS + 1); il++) {
    int l, s;
    if (!job_of<IS_O>(il, l, s)) continue;
    float d[16];
    bool ok = false;
#pragma unroll
    for (int c = 0; c < NC; c++) {
      if (!PRE || !ok) mbar_wait(sb + BAR_GF + 8 * (c % NST), ph ^ ((c / NST) & 1), left);
      if (PRE && c + 1 < NC) ok = mbar_test(sb + BAR_GF + 8 * ((c + 1) % NST), ph ^ (((c + 1) / NST) & 1));
      if (c == 0 && w == (IS_O ? 35 : WW) && tid0 == 0 && tile == 0 && l == 0) WTS(il >> 1, IS_O ? 9 : 1);
      wg_fence();
#pragma unroll
      for (int k = chunk_k<IS_O>(c); k < chunk_k<IS_O>(c + 1); k++) {
        const uint64_t db = IS_O ? a.od[k] : a.pd[BIGG ? k & 31 : (c & 3) * 6 + k - chunk_k<IS_O>(c)];
        if (in_smem<IS_O>(k)) {
          const uint64_t da = desc2(wlo + smem_before<IS_O>(k) * 128, WHI);
          if (IS_O) wgmma_ts32(d, da, db, 1); else wgmma_tt32(d, da, db, 1);
        } else {
          if (IS_O) wgmma_rs32(d, wf[k - smem_before<IS_O>(k)], db, k); else wgmma_rt32(d, wf[k - smem_before<IS_O>(k)], db, k);
        }
      }
      wg_commit();
      if (c > 0) {
        wg_wait<1>();
        if (tid0 == 0) mbar_arrive(sb + BAR_GE + 8 * ((c - 1) % NST));
      }
    }
    ph ^= (NC / NST) & 1;
    wg_wait<0>();
    if (tid0 == 0) mbar_arrive(sb + BAR_GE + 8 * (NST - 1));
    uint8_t* dst = (IS_O ? g_prod[s % MD][l] : g_part[s % MD][l]) + (l ? mo : mo0);
    const uint32_t tag = (s / MD) & 1;
#pragma unroll
    for (int j = 0; j < 4; j++) {
      const uint32_t w0 = pack_h2(d[4 * j], d[4 * j + 1]), w1 = pack_h2(d[4 * j + 2], d[4 * j + 3]);
      const uint32_t r = __shfl_xor_sync(0xffffffffu, (g & 1) ? w0 : w1, 4);
      if (IS_O) st_msg8(dst + j * 10240, (((g & 1) ? r : w0) & ~1u) | tag, (g & 1) ? w1 : r);
      else asm volatile("red.relaxed.gpu.global.add.noftz.v2.f16x2 [%0],{%1,%2};" ::"l"(dst + j * 10240), "r"((g & 1) ? r : w0), "r"((g & 1) ? w1 : r) : "memory");
    }
    __syncwarp();
    if ((tid0 & 31) == 0) {
      if (IS_O) asm volatile("red.release.cta.shared.add.u32 [%0],1;" ::"r"(sb + BAR_H) : "memory");
      else mbar_arrive(sb + BAR_H + 8 + 8 * l);
    }
    if (w == (IS_O ? 35 : WW) && tid0 == 0 && tile == 0) WTS(il >> 1, (IS_O ? 10 : 2) + l);
  }
  if (left <= 0) g_err = 11;
}

__device__ __forceinline__ void work_q_producer(Counters* cnt) {
  using namespace W;
  int left = SPIN_BUDGET;
#pragma unroll 1
  for (int i = 0; i <= NS; i++) {
    const uint8_t* src = opaque(g_xnb[i & 7]);
    cnt_wait_warp(&cnt[CN_L][i][0], (i < NSEG ? 16 : 0) + (i > LAG ? 16 : 0), left);
    if ((int)blockIdx.x == WW) WTS(i, 5);
    fence_async_all();
#pragma unroll 1
    for (int r = 0; r < QR; r++, src += QK * 2048) {
#pragma unroll
      for (int c = 0; c < QST; c++) {
        if (!BIGG && c == QST - 1 && r == 2) break;
        mbar_wait(sb + BAR_QE + 8 * c, ((!BIGG && c < QST - 1 ? i + r : r) & 1) ^ 1, left);
        if (elect()) {
          mbar_expect_tx(sb + BAR_QF + 8 * c, c < QST - 1 ? 8192 : 4096);
          bulk_g2s(sb + OFF_Q + c * 8192, src + c * 8192, c < QST - 1 ? 8192 : 4096, sb + BAR_QF + 8 * c);
        }
      }
    }
  }
}

__device__ __forceinline__ void work_q(const WorkArgs& a, int w, int tid0) {
  using namespace W;
  int left = SPIN_BUDGET;
  const int warp = __shfl_sync(0xffffffffu, tid0 >> 5, 0);
#pragma unroll 1
  for (int i = 0; i <= NS; i++) {
    {
      if (warp == 3 && i + 6 < NSEG && (tid0 & 31) < 20) {
        const int j = tid0 & 31;
        prefetch_l2((j < 10 ? g_xn[0] : reinterpret_cast<const uint8_t*>(a.x0)) + (size_t)(i + 6) * 40960 + (w * 10 + j % 10) * 128);
      }
      __syncwarp();
    }
    {
      float d[32];
#pragma unroll
      for (int r = 0; r < QR; r++) {
#pragma unroll
        for (int c = 0; c < QST; c++) {
          if (QK * r + 4 * c >= 40) break;
          mbar_wait(sb + BAR_QF + 8 * c, (!BIGG && c < QST - 1 ? i + r : r) & 1, left);
          wg_fence();
#pragma unroll
          for (int k = QK * r + 4 * c; k < QK * r + min(4 * c + 4, QK); k++) wgmma_ts64(d, a.qw[2 * k], a.qw[2 * k + 1], k);
          wg_commit();
          if (c < QST - 2 || QK * (r + 1) + 4 * c < 40) {
            wg_wait<0>();
            if (tid0 == 0) mbar_arrive(sb + BAR_QE + 8 * c);
          }
        }
      }
      wg_wait<0>();
      if (w == WW && tid0 == 0) WTS(i, 6);
      const int lane = fresh(tid0) & 31;
      const uint32_t o = sb + OFF_STG + ((lane >> 4) * 8 + (lane & 7)) * PITCH + warp * 32 + (lane & 8) * 2;
      bar_sync(NB_Q, 128);
#pragma unroll
      for (int j = 0; j < 4; j++)
        stsm4t(o + 16 * j * PITCH, pack_bf16(d[8 * j], d[8 * j + 1]), pack_bf16(d[8 * j + 2], d[8 * j + 3]), pack_bf16(d[8 * j + 4], d[8 * j + 5]),
               pack_bf16(d[8 * j + 6], d[8 * j + 7]));
      bar_sync(NB_Q, 128);
    }
#pragma unroll 1
    for (int j = 0; j < 2; j++) {
      int l, s;
      if (!job_of<true>(2 * i + j, l, s)) continue;
      const bool ts = w == WW && (l == 0 || i >= NSEG);
      {
        const int tid = fresh(tid0), tk = tid >> 2, h = tid & 3;
        const float scl = 0.22360679774997896f * 1.4426950408889634f;
        const uint32_t kn = sb + OFF_STG + (l * 32 + tk) * PITCH + 40, ko = sb + OFF_HIST + (l * 14 + 14 + tk) * 80;
        float sc[2];
        {
          float q[20];
#pragma unroll
          for (int j = 0; j < 5; j++) {
            const uint2 u = lds64(kn - 40 + j * 8);
            q[4 * j] = bf_lo(u.x); q[4 * j + 1] = bf_hi(u.x); q[4 * j + 2] = bf_lo(u.y); q[4 * j + 3] = bf_hi(u.y);
          }
#pragma unroll
          for (int e = 0; e < 2; e++) {
            const int d = 4 * h + 2 * e;
            const uint32_t kv = tk >= d ? kn - d * PITCH : ko - d * 80;
            float s0 = 0.f, s1 = 0.f;
#pragma unroll
            for (int n = 0; n < 5; n++) {
              const uint2 u = lds64(kv + n * 8);
              s0 = fmaf(q[4 * n], bf_lo(u.x), s0); s1 = fmaf(q[4 * n + 1], bf_hi(u.x), s1);
              s0 = fmaf(q[4 * n + 2], bf_lo(u.y), s0); s1 = fmaf(q[4 * n + 3], bf_hi(u.y), s1);
            }
            sc[e] = s * 32 + tk >= d ? (s0 + s1) * scl : -INFINITY;
          }
        }
        uint32_t v[8][3];
#pragma unroll
        for (int j = 0; j < 8; j++) {
          const uint32_t kv = (tk >= 2 * j ? kn - 2 * j * PITCH : ko - 2 * j * 80) + 40 + h * 4;
          v[j][0] = lds32(kv); v[j][1] = lds32(kv + 16); v[j][2] = lds32(kv + (h < 2 ? 32 : 0));
        }
        float mx = fmaxf(sc[0], sc[1]);
        mx = fmaxf(fmaxf(mx, __shfl_xor_sync(0xffffffffu, mx, 1)), fmaxf(__shfl_xor_sync(0xffffffffu, mx, 2), __shfl_xor_sync(0xffffffffu, mx, 3)));
        sc[0] = ex2(sc[0] - mx); sc[1] = ex2(sc[1] - mx);
        const float inv = rcp(quad_sum(sc[0] + sc[1]));
        const uint32_t pp = pack_bf16(sc[0] * inv, sc[1] * inv);
        float o[6] = {};
#pragma unroll
        for (int j = 0; j < 4; j++) {
          const uint32_t p = __shfl_sync(0xffffffffu, pp, j, 4);
#pragma unroll
          for (int n = 0; n < 3; n++) {
            o[2 * n] = fmaf(bf_lo(p), bf_lo(v[2 * j][n]), o[2 * n]); o[2 * n + 1] = fmaf(bf_lo(p), bf_hi(v[2 * j][n]), o[2 * n + 1]);
            o[2 * n] = fmaf(bf_hi(p), bf_lo(v[2 * j + 1][n]), o[2 * n]); o[2 * n + 1] = fmaf(bf_hi(p), bf_hi(v[2 * j + 1][n]), o[2 * n + 1]);
          }
        }
        const int c = w * 10 + h;
        uint8_t* img = g_ob[s & 7][l] + tk * 16 + (c >> 2) * 512 + (c & 3) * 4;
#pragma unroll
        for (int n = 0; n < 3; n++)
          if (n < 2 || h < 2) *reinterpret_cast<uint32_t*>(img + n * 512) = pack_bf16(o[2 * n], o[2 * n + 1]);
      }
      bar_arrive(NB_A + l, 160);
      if (ts && tid0 == 0) WTS(i, 15);
    }
    bar_sync(NB_Q, 128);
    {
      const int tid = fresh(tid0), r = tid >> 3, c = tid & 7;
      if (r < 14 && c < 5) {
        const uint32_t p = sb + OFF_STG + (18 + r) * PITCH + 40 + c * 16, h = sb + OFF_HIST + r * 80 + c * 16;
        const uint2 u0 = lds64(p), v0 = lds64(p + 8), u1 = lds64(p + 32 * PITCH), v1 = lds64(p + 32 * PITCH + 8);
        sts128(h, make_uint4(u0.x, u0.y, v0.x, v0.y));
        if (i > LAG) sts128(h + 1120, make_uint4(u1.x, u1.y, v1.x, v1.y));
      }
      __syncwarp();
    }
    fence_async();
    bar_sync(NB_A + 2, 160);
    if (tid0 < 2) mbar_arrive(sb + BAR_QE + 8 * (QST - 2 + tid0));
    __syncwarp();
  }
  if (left <= 0) g_err = 12;
}

__device__ __forceinline__ void work_f(const WorkArgs& a, int w, int tid0, Counters* cnt) {
  using namespace W;
  int left = SPIN_BUDGET;
  uint32_t passes = 0;
  const int warp = __shfl_sync(0xffffffffu, tid0 >> 5, 0), grp = w - 32;
#pragma unroll 1
  for (int n = 0; n < 2 * (NS + 1); n++) {
    int l, s;
    if (!job_of<true>(n, l, s)) continue;
    const int lane = fresh(tid0) & 31;
    cnt_wait_warp(&cnt[CN_A][s][l * 32], 32, left);
    uint32_t r[20];
    uint4 x[5];
    const uint8_t* res = g_xs[2 * l] + (uint32_t)(s * 40960 + grp * 10240);
    const uint8_t* src = g_prod[s % MD][l] + grp * 10240;
    if (l) load20(r, res + (warp * 2560 + lane * 16), 512);
    else load20(r, res + ((lane & 3) * 2560 + warp * 640 + (lane >> 2) * 16), 128);
    pass_wait(passes += 8, left);
    if (HD) { const uint32_t t0 = clk32(); while (clk32() - t0 < HD) {} }
    if (l) poll5(x, src + (warp * 64 + (lane >> 2) * 256 + (lane & 3) * 16), 2048, (s / MD) & 1, left);
    else poll5(x, src + (warp * 2560 + lane * 16), 512, (s / MD) & 1, left);
    add_product(r, x);
    if (l == 0) {
      uint8_t* xp = g_xs[1] + (uint32_t)(s * 40960 + grp * 10240 + warp * 2560 + lane * 16);
#pragma unroll
      for (int j = 0; j < 5; j++) *reinterpret_cast<uint4*>(xp + j * 512) = make_uint4(r[4 * j], r[4 * j + 1], r[4 * j + 2], r[4 * j + 3]);
      float m, q;
      pair_stats<4>(r, m, q, lane);
      if (!(lane & 12)) asm volatile("st.shared.v2.f32 [%0],{%1,%2};" ::"r"(sb + OFF_ST + (lane & 3) * 64 + (lane & 16) * 2 + warp * 8), "f"(m), "f"(q) : "memory");
      const bool odd = lane & 4;
      const uint32_t keep = odd ? 0x7632 : 0x5410, give = odd ? 0x5410 : 0x7632;
#pragma unroll
      for (int j = 0; j < 20; j += 4) {
        const uint32_t k0 = __byte_perm(r[j], r[j + 1], keep), k1 = __byte_perm(r[j + 2], r[j + 3], keep);
        const uint32_t g0 = __shfl_xor_sync(0xffffffffu, __byte_perm(r[j], r[j + 1], give), 4), g1 = __shfl_xor_sync(0xffffffffu, __byte_perm(r[j + 2], r[j + 3], give), 4);
        r[j] = odd ? g0 : k0; r[j + 1] = odd ? g1 : k1; r[j + 2] = odd ? k0 : g0; r[j + 3] = odd ? k1 : g1;
      }
      bar_sync(NB_Q, 128);
      const uint32_t sa = sb + OFF_ST + (lane & 3) * 64 + (lane & 4) * 8;
      const uint4 e0 = lds128(sa), e1 = lds128(sa + 16);
      m = 0.25f * ((F(e0.x) + F(e0.z)) + (F(e1.x) + F(e1.z)));
      q = rsqrtf(((part_var(F(e0.x), F(e0.y), 160.f, m) + part_var(F(e0.z), F(e0.w), 160.f, m)) +
                  (part_var(F(e1.x), F(e1.y), 160.f, m) + part_var(F(e1.z), F(e1.w), 160.f, m))) * (1.f / DM) + 1e-5f);
      m *= -q;
      uint8_t* dst = g_xn[1] + (uint32_t)((s * 4 + grp) * 10240 + (warp * 20 + (lane >> 3)) * 128 + (lane & 3) * 32 + (lane & 4) * 4);
#define NRM(V) pack_bf16(fmaf(bf_lo(V), q, m), fmaf(bf_hi(V), q, m))
#pragma unroll
      for (int j = 0; j < 20; j += 4) *reinterpret_cast<uint4*>(dst + j * 128) = make_uint4(NRM(r[j]), NRM(r[j + 1]), NRM(r[j + 2]), NRM(r[j + 3]));
#undef NRM
      bar_sync(NB_Q, 128);
      if (warp == 0 && elect()) cnt_signal(&cnt[CN_X][s][0]);
      __syncwarp();
    } else {
      uint2* dst = reinterpret_cast<uint2*>(a.out) + (uint32_t)((s * 16 + grp * 4 + warp) * 320 + lane);
#pragma unroll
      for (int j = 0; j < 20; j += 4) {
        dst[j * 8] = make_uint2(__byte_perm(r[j], r[j + 1], 0x5410), __byte_perm(r[j + 2], r[j + 3], 0x5410));
        dst[160 + j * 8] = make_uint2(__byte_perm(r[j], r[j + 1], 0x7632), __byte_perm(r[j + 2], r[j + 3], 0x7632));
      }
    }
    if (w == 35 && tid0 == 0) WTS(n >> 1, 12 + l);
  }
  if (left <= 0) g_err = 13;
}
#undef F

__global__ void __launch_bounds__(512, 1)
k_work(const __grid_constant__ CUtensorMap tmWo, const __grid_constant__ CUtensorMap tmBo, const __grid_constant__ WorkArgs args) {
  using namespace W;
  extern __shared__ __align__(1024) uint8_t smem[];
  const int tid = threadIdx.x, w = blockIdx.x;
  const int wg = __shfl_sync(0xffffffffu, tid >> 7, 0);
  const int tid0 = __shfl_sync(0xffffffffu, tid & 127, tid & 31);
  if (tid == 0) {
    if (smem_u32(smem) != sb) g_err = 101;
    for (int i = 0; i < 8; i++) { mbar_init(sb + BAR_GF + 8 * i, 1); mbar_init(sb + BAR_GE + 8 * i, 2); }
    for (int i = 0; i < QST; i++) { mbar_init(sb + BAR_QF + 8 * i, 1); mbar_init(sb + BAR_QE + 8 * i, 1); }
    mbar_init(sb + BAR_W1, 1); mbar_init(sb + BAR_W2, 1); sts32(sb + BAR_H, 0); mbar_init(sb + BAR_H + 8, 8); mbar_init(sb + BAR_H + 16, 8);
    asm volatile("fence.mbarrier_init.release.cluster;" ::: "memory");
    fence_async();
    mbar_expect_tx(sb + BAR_W1, (w < NP ? 82 : 78) * 2048);
    mbar_expect_tx(sb + BAR_W2, (w < NP ? 46 : 2) * 2048);
  }
  Counters* cnt = g_cnt[launch_parity()];
  if (WDL && wg == 3) {
    int left = SPIN_BUDGET;
    cnt_wait_warp(&cnt[CN_Z][0][32], 96, left);
  }
  __syncthreads();

  if (wg < 2 && w < NP) {
    asm volatile("setmaxnreg.inc.sync.aligned.u32 208;");
    work_g<false>(args, w, wg, tid0, cnt);
  } else if (wg < 2) {
    asm volatile("setmaxnreg.inc.sync.aligned.u32 200;");
    if (w >= OW0) work_g<true>(args, w, wg, tid0, cnt);
    else {
      bar_sync(NB_PRO, 512);
      work_l(args, tid0 & 31, 12 + __shfl_sync(0xffffffffu, tid0 >> 5, 0), 1 << wg, cnt);
    }
  } else if (wg == 2 && w < 32) {
    asm volatile("setmaxnreg.dec.sync.aligned.u32 72;");
    for (int i = tid0; i < MD * 160; i += 128) reinterpret_cast<uint4*>(g_part[i / 160][w >> 4] + (w & 15) * 2560)[i % 160] = make_uint4(0, 0, 0, 0);
    bar_sync(NB_Q, 128);
    if (tid0 == 0) cnt_signal(&cnt[CN_Z][0][0]);
    for (int i = tid0; i < 560; i += 128) sts32(sb + OFF_HIST + i * 4, 0);
    bar_sync(NB_PRO, 512);
#pragma unroll 16
    for (int i = tid0; i < 640 * 32; i += 128) {
      const int k = i >> 5, c = i & 31;
      uint32_t v = 0;
      if (c < 30) v = *reinterpret_cast<const uint32_t*>(args.wqkv + (size_t)k * 1920 + (c / 10) * 640 + w * 20 + (c % 10) * 2);
      sts32(sb + OFF_WQ + (k >> 6) * 8192 + (k & 63) * 128 + (((c >> 2) ^ (k & 7)) << 4) + (c & 3) * 4, v);
    }
    fence_async();
    bar_sync(NB_Q, 128);
    work_q(args, w, tid0);
  } else if (wg == 2) {
    asm volatile("setmaxnreg.dec.sync.aligned.u32 56;");
    for (int i = tid0; i < MD * 1280; i += 128) reinterpret_cast<uint4*>(g_prod[i / 1280][(i / 640) & 1] + (w - 32) * (4 * 2560))[i % 640] = make_uint4(SENT, SENT, SENT, SENT);
    bar_sync(NB_Q, 128);
    if (tid0 == 0) cnt_signal(&cnt[CN_Z][0][0]);
    bar_sync(NB_PRO, 512);
    work_f(args, w, tid0, cnt);
  } else if (w >= 32) {
    asm volatile("setmaxnreg.dec.sync.aligned.u32 56;");
    const int warp = __shfl_sync(0xffffffffu, tid0 >> 5, 0);
    if (elect()) work_g_weights<true>(tmBo, w, warp, false);
    __syncwarp();
    bar_sync(NB_PRO, 512);
    if (elect()) work_g_weights<true>(tmBo, w, warp, true);
    __syncwarp();
    if (warp == 0) work_g_producer<true>(w, cnt);
    else work_l(args, tid0 & 31, (w - 32) * 3 + warp - 1, 3, cnt);
  } else {
    asm volatile("setmaxnreg.dec.sync.aligned.u32 24;");
    const int warp = __shfl_sync(0xffffffffu, tid0 >> 5, 0);
    if (elect()) {
      if (w < NP) work_g_weights<false>(tmWo, w, warp, false);
      else if (w >= OW0) work_g_weights<true>(tmBo, w, warp, false);
    }
    __syncwarp();
    bar_sync(NB_PRO, 512);
    if (elect()) {
      if (w < NP) work_g_weights<false>(tmWo, w, warp, true);
      else if (w >= OW0) work_g_weights<true>(tmBo, w, warp, true);
    }
    __syncwarp();
    if (warp == 0) {
      if (w < NP) work_g_producer<false>(w, cnt);
      else if (w >= OW0) work_g_producer<true>(w, cnt);
    } else if (warp == 1) {
      work_q_producer(cnt);
    } else if (warp == 2) {
      int left = SPIN_BUDGET;
#pragma unroll 1
      for (int n = 0; n < 2 * NS; n++) {
        int l, s;
        if (w >= NP || !job_of<false>(n, l, s)) continue;
        mbar_wait(sb + BAR_H + 8 + 8 * l, s & 1, left);
        if (elect()) cnt_signal(&cnt[CN_P][s][l * 32]);
        __syncwarp();
      }
    } else {
#pragma unroll 1
      for (int n = 0; n < 2 * (NS + 1); n++) {
        int l, s;
        const bool on = job_of<true>(n, l, s);
        if (on) bar_sync(NB_A + l, 160);
        if (n & 1) bar_arrive(NB_A + 2, 160);
        if (!on) continue;
        if (elect()) cnt_signal(&cnt[CN_A][s][l * 32]);
        __syncwarp();
        if (w == WW && tid0 == 96 && (l == 0 || n >= 2 * NSEG)) WTS(n >> 1, 7);
      }
    }
  }
  asm volatile("griddepcontrol.wait;" ::: "memory");
  if (w == 35 && tid == 256) g_launch = ld_relaxed(&g_launch) + 1;
}

typedef CUresult (*EncodeFn)(CUtensorMap*, CUtensorMapDataType, cuuint32_t, void*, const cuuint64_t*, const cuuint64_t*,
                             const cuuint32_t*, const cuuint32_t*, CUtensorMapInterleave, CUtensorMapSwizzle,
                             CUtensorMapL2promotion, CUtensorMapFloatOOBfill);

static void make_map(EncodeFn enc, CUtensorMap* tm, const void* ptr, uint64_t cols, uint64_t rows, uint32_t boxc, uint32_t boxr,
                     CUtensorMapSwizzle sw = CU_TENSOR_MAP_SWIZZLE_128B, CUtensorMapL2promotion pr = CU_TENSOR_MAP_L2_PROMOTION_L2_256B) {
  cuuint64_t dims[2] = {cols, rows};
  cuuint64_t strides[1] = {cols * 2};
  cuuint32_t box[2] = {boxc, boxr};
  cuuint32_t es[2] = {1, 1};
  enc(tm, CU_TENSOR_MAP_DATA_TYPE_BFLOAT16, 2, const_cast<void*>(ptr), dims, strides, box, es, CU_TENSOR_MAP_INTERLEAVE_NONE,
      sw, pr, CU_TENSOR_MAP_FLOAT_OOB_FILL_NONE);
}

extern "C" void kernel_launch(void* const* d_in, const int* in_sizes, int n_in, void* d_out, int out_size) {
  const bf16* x0 = (const bf16*)d_in[0];
  const bf16* mem0 = (const bf16*)d_in[1];
  const bf16* Wq = (const bf16*)d_in[2];
  const bf16* Wk = (const bf16*)d_in[3];
  const bf16* Wv = (const bf16*)d_in[4];
  const bf16* Wo = (const bf16*)d_in[5];
  const bf16* Bqkv = (const bf16*)d_in[8];
  const bf16* Bwo = (const bf16*)d_in[9];
  bf16* out = (bf16*)d_out;

  static EncodeFn enc = nullptr;
  static uint8_t *p_xn, *p_o, *p_mbuf, *p_mail, *p_rot, *p_cnt;
  if (!enc) {
    void* fn = nullptr;
    cudaDriverEntryPointQueryResult qr;
    cudaGetDriverEntryPoint("cuTensorMapEncodeTiled", &fn, cudaEnableDefault, &qr);
    enc = (EncodeFn)fn;
    cudaFuncSetAttribute(k_chain, cudaFuncAttributeMaxDynamicSharedMemorySize, C::SMEM);
    cudaFuncSetAttribute(k_work, cudaFuncAttributeMaxDynamicSharedMemorySize, W::SMEM);
    void* p;
    cudaGetSymbolAddress(&p, g_xn); p_xn = (uint8_t*)p;
    cudaGetSymbolAddress(&p, g_o); p_o = (uint8_t*)p;
    cudaGetSymbolAddress(&p, g_mbuf); p_mbuf = (uint8_t*)p;
    cudaGetSymbolAddress(&p, g_mail); p_mail = (uint8_t*)p;
    cudaGetSymbolAddress(&p, g_cnt); p_cnt = (uint8_t*)p;
    cudaGetSymbolAddress(&p, g_rot); p_rot = (uint8_t*)p;
  }
  CUtensorMap tmWq, tmWk, tmWv, tmWo, tmWo16, tmBo, tmX;
  make_map(enc, &tmWq, Wq, NH * DH, DM, 64, 64);
  make_map(enc, &tmWk, Wk, NH * DH, DM, 64, 64);
  make_map(enc, &tmWv, Wv, NH * DH, DM, 64, 64);
  make_map(enc, &tmWo, Wo, DM, NH * DH, 64, 64);
  make_map(enc, &tmWo16, Wo, DM, NH * DH, 64, 16);
  make_map(enc, &tmBo, Bwo, DM, DM, 64, 16);
  {
    cuuint64_t dims[3] = {2560, 4 * NS, 2};
    cuuint64_t strides[2] = {10240, (cuuint64_t)(256 - 4 * LAG) * 10240};
    cuuint32_t box[3] = {256, 3, 2};
    cuuint32_t es[3] = {1, 1, 1};
    enc(&tmX, CU_TENSOR_MAP_DATA_TYPE_UINT32, 3, p_xn, dims, strides, box, es, CU_TENSOR_MAP_INTERLEAVE_NONE,
        CU_TENSOR_MAP_SWIZZLE_NONE, CU_TENSOR_MAP_L2_PROMOTION_NONE, CU_TENSOR_MAP_FLOAT_OOB_FILL_NONE);
  }

  cudaStream_t st = cudaStreamPerThread;
  ChainArgs ca;
  ca.x0 = x0; ca.mem0 = mem0; ca.wo = Wo;
  ca.xn = p_xn;
  ca.oimg = p_o;
  ca.mbuf = p_mbuf; ca.mail = p_mail; ca.rot = p_rot; ca.cnt = (Counters*)p_cnt;
  k_chain<<<96, 384, C::SMEM, st>>>(ca, tmWq, tmWk, tmWv, tmWo, tmX);
  WorkArgs wa;
  fill_descs(wa);
  wa.x0 = x0; wa.out = out;
  wa.wqkv = Bqkv;
  cudaLaunchAttribute at[1];
  at[0].id = cudaLaunchAttributeProgrammaticStreamSerialization; at[0].val.programmaticStreamSerializationAllowed = 1;
  cudaLaunchConfig_t cfg = {};
  cfg.gridDim = dim3(W::NW); cfg.blockDim = dim3(512); cfg.dynamicSmemBytes = W::SMEM; cfg.stream = st;
  cfg.attrs = at; cfg.numAttrs = 1;
  cudaLaunchKernelEx(&cfg, k_work, tmWo16, tmBo, wa);
}
```
